```python
import torch

def _softmax(x, axis=-1):
    return torch.softmax(x, dim=axis)
def _gelu(x):
    return torch.nn.functional.gelu(x, approximate="tanh")
def _silu(x):
    return torch.nn.functional.silu(x)
def _sigmoid(x):
    return torch.sigmoid(x)
def _layernorm(x, axis=-1, eps=1e-5):
    m = x.mean(dim=axis, keepdim=True)
    v = x.var(dim=axis, keepdim=True, unbiased=False)
    return (x - m) / torch.sqrt(v + eps)
def _scatter_add(tgt, idx, src, axis=0):
    return tgt.clone().index_add_(axis, idx, src)
def _segment_sum(src, seg, n):
    out = torch.zeros((n,) + src.shape[1:], dtype=src.dtype)
    return out.index_add_(0, seg, src)
def _pad(x, pw):
    flat = tuple(v for pair in reversed(pw) for v in pair)
    return torch.nn.functional.pad(x, flat)

kernel_name = 'concat_heads__linear_attn_block__grouped_kv_mqa__prompt'

def setup_inputs():

    _w = (lambda a: (lambda t: t.to(torch.bfloat16) if t.is_floating_point() else t)(torch.as_tensor(a)))
    def _A_setup():
        B, S, D = 1, 2048, 1024
        return {
            "x": _w((lambda *s: torch.randn(*s, dtype=torch.bfloat16) * 0.05)(B, S, D)),
            "wqkv": _w((lambda *s: torch.randn(*s, dtype=torch.bfloat16) * 0.8)(D, 3 * D)),
            "wo": _w((lambda *s: torch.randn(*s, dtype=torch.bfloat16) * 0.05)(D, D)),
        }
    _A_in = _A_setup()

    def _B_setup():
        B, S, D, H = 1, 2048, 1024, 32
        Dh = D // H
        return {
            "x": _w((lambda *s: torch.randn(*s, dtype=torch.bfloat16) * 0.05)(B, S, D)),
            "wq": _w((lambda *s: torch.randn(*s, dtype=torch.bfloat16) * 0.8)(D, H * Dh)),
            "wk": _w((lambda *s: torch.randn(*s, dtype=torch.bfloat16) * 0.8)(D, Dh)),
            "wv": _w((lambda *s: torch.randn(*s, dtype=torch.bfloat16) * 0.05)(D, Dh)),
            "wo": _w((lambda *s: torch.randn(*s, dtype=torch.bfloat16) * 0.05)(H * Dh, D)),
        }
    _B_in = _B_setup()

    return {
        "A_x": _A_in["x"],
        "A_wqkv": _A_in["wqkv"],
        "A_wo": _A_in["wo"],
        "B_x": _B_in["x"],
        "B_wq": _B_in["wq"],
        "B_wk": _B_in["wk"],
        "B_wv": _B_in["wv"],
        "B_wo": _B_in["wo"],
    }

def reference(A_x, A_wqkv, A_wo, B_x, B_wq, B_wk, B_wv, B_wo):
    def _A_ref(x, wqkv, wo):
        B, S, D = x.shape
        H = 32; Dh = D // H
        qkv = (lambda x, *d: x.permute(*d))((x @ wqkv).reshape(B, S, 3, H, Dh), 2, 0, 3, 1, 4)
        q, k, v = qkv[0], qkv[1], qkv[2]
        phi = lambda t: torch.where(t > 0, t + 1, torch.exp(t)) + 1e-6
        pq, pk = phi(q), phi(k)
        kv = torch.einsum("bhsd,bhse->bhde", pk, v)
        z = torch.einsum("bhsd->bhd", pk)
        num = torch.einsum("bhqd,bhde->bhqe", pq, kv)
        den = torch.einsum("bhqd,bhd->bhq", pq, z)[..., None] + 1e-6
        o = num / den
        return (lambda x, *d: x.permute(*d))(o, 0, 2, 1, 3).reshape(B, S, D) @ wo

    def _B_ref(x, wq, wk, wv, wo):
        B, S, D = x.shape
        H = 32
        Dh = D // H
        q = (lambda x, *d: x.permute(*d))((x @ wq).reshape(B, S, H, Dh), 0, 2, 1, 3)
        k = x @ wk
        v = x @ wv
        scores = torch.einsum("bhqd,bkd->bhqk", q, k) * (Dh ** -0.5)
        p = _softmax(scores, axis=-1)
        o = torch.einsum("bhqk,bkd->bhqd", p, v)
        return (lambda x, *d: x.permute(*d))(o, 0, 2, 1, 3).reshape(B, S, H * Dh) @ wo

    a = _A_ref(A_x, A_wqkv, A_wo)
    b = _B_ref(B_x, B_wq, B_wk, B_wv, B_wo)
    return torch.concatenate([a, b], axis=-1)
```

```cpp
#include <cuda_runtime.h>
#include <cuda_bf16.h>
#include <cuda.h>
#include <stdint.h>

namespace {

constexpr int NS = 4;
constexpr int STAGE = 32768, BLK = 8192;
constexpr int NKV = 4;
constexpr int KVB = 16384;
constexpr int OFF_B = NS * 16384;
constexpr int OFF_STG = OFF_B + NS * 16384;
constexpr int OFF_KV = OFF_STG + 32768;
constexpr int OFF_OWN = OFF_KV + 3 * KVB;
constexpr int OFF_ONE = OFF_KV + NKV * KVB;
constexpr int OFF_BAR = OFF_ONE + 1024;
constexpr int SMEM_BYTES = OFF_BAR + 512;
constexpr int B_XS = 56, B_FULL = 64, B_EMPTY = B_FULL + 8 * NS, B_KVF = B_EMPTY + 8 * NS, B_KVE = B_KVF + 8 * NKV,
              B_LAST = B_KVE + 8 * NKV, B_PUBA = B_LAST + 64, B_PUBG = B_PUBA + 24, B_PREP = B_PUBG + 8, B_ALLKV = B_PREP + 8,
              B_KVPUB = B_ALLKV + 8, B_QDONE = B_KVPUB + 8, B_KVBOTH = B_QDONE + 8, B_RED = B_KVBOTH + 8, B_SUM = B_RED + 8,
              B_KVMMA = B_SUM + 8, B_Q3 = B_KVMMA + 8, B_PART = B_Q3 + 8, B_FIN = B_PART + 8, B_GO = B_FIN + 8, B_EPOCH = 8 * 48;
constexpr uint32_t bar_count(int o) {
    return (o >= B_EMPTY && o < B_KVF) || (o >= B_KVE && o < B_LAST) || o == B_PUBG || o == B_KVMMA ? 4
         : (o >= B_PUBA && o < B_PUBG) || o == B_Q3 ? 8 : o == B_PREP || o == B_KVBOTH || o == B_FIN ? 2 : 1;
}
constexpr uint64_t bar_counts(int c) {
    uint64_t v = 0;
    for (int g = 0; g < 16; g++) v |= (uint64_t)bar_count(8 * (3 * g + c)) << (4 * g);
    return v;
}
constexpr uint64_t BC0 = bar_counts(0), BC1 = bar_counts(1), BC2 = bar_counts(2);
constexpr int F_KV = 0, F_SUM = 32 * 32, F_OA = F_SUM + 32 * 8, F_OB = F_OA + 32 * 16, F_Q3 = F_OB + 32 * 16,
              F_PART = F_Q3 + 128, F_DONE = F_PART + 32 * 4, F_K0 = F_DONE + 16, F_TOTAL = F_DONE + 32;
constexpr float LOG2E = 1.4426950408889634f;
constexpr float QSCALE = 0.17677669529663687f * LOG2E;

struct alignas(64) Params {
    CUtensorMap xB, wq, xA, wqkv, oa, woA, ob, woB, out;
    const uint4 *wk, *wv;
    uint4* outp;
    int nstage;
};

constexpr int QS = 128 * 256, K0 = 8 * QS;
struct Scratch {
    __nv_bfloat16 oa[2048 * 1024];
    __nv_bfloat16 ob[2048 * 1024];
    __nv_bfloat16 kv[4096 * 32];
    uint4 q[K0 + 2048 * 4];
    float4 part[256 * 5 * 128];
    float acc[32 * 1056];
    unsigned flag[F_TOTAL];
};
__device__ __align__(1024) Scratch g_s;
#define g_oa g_s.oa
#define g_ob g_s.ob
#define g_kv g_s.kv
#define g_q g_s.q
#define g_part g_s.part
#define g_acc g_s.acc
#define g_flag g_s.flag

__device__ __forceinline__ void mbar_init(uint32_t a, uint32_t c) { asm volatile("mbarrier.init.shared::cta.b64 [%0], %1;" :: "r"(a), "r"(c) : "memory"); }
__device__ __forceinline__ void mbar_expect(uint32_t a, uint32_t b) { asm volatile("mbarrier.arrive.expect_tx.shared::cta.b64 _, [%0], %1;" :: "r"(a), "r"(b) : "memory"); }
__device__ __forceinline__ void mbar_arrive(uint32_t a) { asm volatile("mbarrier.arrive.shared::cta.b64 _, [%0];" :: "r"(a) : "memory"); }
__device__ __forceinline__ void mbar_arrive_cl(uint32_t a, uint32_t cnt, bool pred) {
    asm volatile("{\n.reg .pred p;\nsetp.ne.u32 p, %2, 0;\n@p mbarrier.arrive.shared::cluster.b64 _, [%0], %1;\n}" :: "r"(a), "r"(cnt), "r"((uint32_t)pred) : "memory");
}
__device__ __forceinline__ bool mbar_try(uint32_t a, uint32_t ph) {
    uint32_t ok;
    asm volatile("{\n.reg .pred p;\nmbarrier.try_wait.parity.shared::cta.b64 p, [%1], %2;\nselp.u32 %0, 1, 0, p;\n}" : "=r"(ok) : "r"(a), "r"(ph) : "memory");
    return ok;
}
__device__ __forceinline__ bool mbar_test(uint32_t a, uint32_t ph) {
    uint32_t ok;
    asm volatile("{\n.reg .pred p;\nmbarrier.test_wait.parity.shared::cta.b64 p, [%1], %2;\nselp.u32 %0, 1, 0, p;\n}" : "=r"(ok) : "r"(a), "r"(ph) : "memory");
    return ok;
}
__device__ __forceinline__ void mbar_wait(uint32_t a, uint32_t ph) {
    asm volatile("{\n.reg .pred p;\nW:\nmbarrier.try_wait.parity.shared::cta.b64 p, [%0], %1;\n@!p bra W;\n}" :: "r"(a), "r"(ph) : "memory");
}
__device__ __forceinline__ void watchdog(uint32_t& n, uint32_t& t0) {
    if ((++n & 255) == 0) {
        uint32_t t;
        asm volatile("mov.u32 %0, %%globaltimer_lo;" : "=r"(t));
        if (n == 256) t0 = t; else if (t - t0 > 2000000000u) __trap();
    }
}
__device__ __forceinline__ void mbar_wait_wd(uint32_t a, uint32_t ph) {
    uint32_t n = 0, t0 = 0;
    while (!mbar_try(a, ph)) watchdog(n, t0);
}
__device__ __forceinline__ uint32_t mapa(uint32_t a, uint32_t cta) { uint32_t r; asm("mapa.shared::cluster.u32 %0, %1, %2;" : "=r"(r) : "r"(a), "r"(cta)); return r; }
__device__ __forceinline__ void tma_ld(uint32_t dst, const CUtensorMap* m, int c0, int c1, uint32_t bar) {
    asm volatile("cp.async.bulk.tensor.2d.shared::cluster.global.mbarrier::complete_tx::bytes [%0], [%1, {%3, %4}], [%2];"
        :: "r"(dst), "l"(m), "r"(bar), "r"(c0), "r"(c1) : "memory");
}
__device__ __forceinline__ void tma_ld_mc(uint32_t dst, const CUtensorMap* m, int c0, int c1, uint32_t bar) {
    asm volatile("cp.async.bulk.tensor.2d.shared::cluster.global.mbarrier::complete_tx::bytes.multicast::cluster [%0], [%1, {%3, %4}], [%2], %5;"
        :: "r"(dst), "l"(m), "r"(bar), "r"(c0), "r"(c1), "h"((uint16_t)3) : "memory");
}
__device__ __forceinline__ void tma_ld_w(uint32_t dst, const CUtensorMap* m, int r, int grp, int nblk, uint32_t bar) {
    asm volatile("cp.async.bulk.tensor.4d.shared::cluster.global.mbarrier::complete_tx::bytes [%0], [%1, {0, %3, %4, %5}], [%2];"
        :: "r"(dst), "l"(m), "r"(bar), "r"(r), "r"(grp), "r"(nblk) : "memory");
}
__device__ __forceinline__ bool elect() {
    uint32_t p;
    asm volatile("{\n.reg .pred p;\nelect.sync _|p, 0xffffffff;\nselp.u32 %0, 1, 0, p;\n}" : "=r"(p));
    return p;
}
__device__ __forceinline__ void bulk_ld_mc(uint32_t dst, const void* src, uint32_t bytes, uint32_t bar) {
    asm volatile("cp.async.bulk.shared::cluster.global.mbarrier::complete_tx::bytes.multicast::cluster [%0], [%1], %2, [%3], %4;"
        :: "r"(dst), "l"(src), "r"(bytes), "r"(bar), "h"((uint16_t)3) : "memory");
}
__device__ __forceinline__ void bulk_ld(uint32_t dst, const void* src, uint32_t bytes, uint32_t bar) {
    asm volatile("cp.async.bulk.shared::cluster.global.mbarrier::complete_tx::bytes [%0], [%1], %2, [%3];"
        :: "r"(dst), "l"(src), "r"(bytes), "r"(bar) : "memory");
}
__device__ __forceinline__ void bulk_s2s(uint32_t dst, uint32_t src, uint32_t bytes, uint32_t bar, uint32_t cta) {
    asm volatile("cp.async.bulk.shared::cluster.shared::cta.mbarrier::complete_tx::bytes [%0], [%1], %2, [%3];"
        :: "r"(mapa(dst, cta)), "r"(src), "r"(bytes), "r"(mapa(bar, cta)) : "memory");
}
__device__ __forceinline__ void st_async4(uint32_t a, uint4 v, uint32_t bar) {
    asm volatile("st.async.weak.shared::cluster.mbarrier::complete_tx::bytes.v4.b32 [%0], {%1, %2, %3, %4}, [%5];"
        :: "r"(a), "r"(v.x), "r"(v.y), "r"(v.z), "r"(v.w), "r"(bar) : "memory");
}
__device__ __forceinline__ void tma_st(const CUtensorMap* m, uint32_t src, int c0, int c1) {
    asm volatile("cp.async.bulk.tensor.2d.global.shared::cta.bulk_group [%0, {%2, %3}], [%1];" :: "l"(m), "r"(src), "r"(c0), "r"(c1) : "memory");
}
__device__ __forceinline__ void fence_async_smem() { asm volatile("fence.proxy.async.shared::cta;" ::: "memory"); }
__device__ __forceinline__ void fence_async_gmem() { asm volatile("fence.proxy.async.global;" ::: "memory"); }
__device__ __forceinline__ unsigned ld_acq(const unsigned* p) { unsigned v; asm volatile("ld.acquire.gpu.global.u32 %0, [%1];" : "=r"(v) : "l"(p) : "memory"); return v; }
__device__ __forceinline__ void publish(unsigned* p) {
    fence_async_gmem();
    asm volatile("red.release.gpu.global.add.u32 [%0], 1;" :: "l"(p) : "memory");
}
__device__ __forceinline__ void poll(const unsigned* p, unsigned target) {
    uint32_t n = 0, t0 = 0;
    while (!__all_sync(0xffffffffu, (int)(ld_acq(p) - target) >= 0)) watchdog(n, t0);
    __syncwarp();
}
__device__ __forceinline__ void wg_fence() { asm volatile("wgmma.fence.sync.aligned;" ::: "memory"); }
__device__ __forceinline__ void wg_commit() { asm volatile("wgmma.commit_group.sync.aligned;" ::: "memory"); }
template <int N> __device__ __forceinline__ void wg_wait() { asm volatile("wgmma.wait_group.sync.aligned %0;" :: "n"(N) : "memory"); }
__device__ __forceinline__ void wg_bar(int id) { asm volatile("bar.sync %0, 128;" :: "r"(id) : "memory"); }
constexpr uint32_t SBASE = 1024;
__device__ __forceinline__ constexpr uint32_t mkdesc(uint32_t off, uint32_t lbo) { return ((SBASE + off) >> 4) | ((lbo >> 4) << 16); }
__device__ __forceinline__ float ex2(float x) { float y; asm("ex2.approx.ftz.f32 %0, %1;" : "=f"(y) : "f"(x)); return y; }
__device__ __forceinline__ float rcp(float x) { float y; asm("rcp.approx.ftz.f32 %0, %1;" : "=f"(y) : "f"(x)); return y; }
__device__ __forceinline__ uint32_t pack(float lo, float hi) { uint32_t r; asm("cvt.rn.bf16x2.f32 %0, %1, %2;" : "=r"(r) : "f"(hi), "f"(lo)); return r; }
template <int N> __device__ __forceinline__ void pin(float (&d)[N]) {
#pragma unroll
    for (int i = 0; i < N; i++) asm volatile("" : "+f"(d[i]) :: "memory");
}
template <int N> __device__ __forceinline__ void pin(uint32_t (&d)[N]) {
#pragma unroll
    for (int i = 0; i < N; i++) asm volatile("" : "+r"(d[i]) :: "memory");
}
template <int N> __device__ __forceinline__ void zero(float (&d)[N]) {
#pragma unroll
    for (int i = 0; i < N; i++) d[i] = 0.f;
    pin(d);
}
__device__ __forceinline__ void sts128(uint32_t a, uint32_t x, uint32_t y, uint32_t z, uint32_t w) {
    asm volatile("st.shared.v4.b32 [%0], {%1, %2, %3, %4};" :: "r"(a), "r"(x), "r"(y), "r"(z), "r"(w) : "memory");
}
template <int N> __device__ __forceinline__ void force(const uint32_t (&r)[N]) {
#pragma unroll
    for (int i = 0; i < N; i += 4)
        asm volatile("{\n.reg .pred p;\nsetp.ne.u32 p, %4, 0;\n@p st.shared.v4.b32 [%4], {%0, %1, %2, %3};\n}"
            :: "r"(r[i]), "r"(r[i + 1]), "r"(r[i + 2]), "r"(r[i + 3]), "r"(threadIdx.y) : "memory");
}
__device__ __forceinline__ void lds128(uint32_t a, uint32_t& x, uint32_t& y, uint32_t& z, uint32_t& w) {
    asm volatile("ld.shared.v4.b32 {%0, %1, %2, %3}, [%4];" : "=r"(x), "=r"(y), "=r"(z), "=r"(w) : "r"(a) : "memory");
}
__device__ __forceinline__ uint32_t lds32(uint32_t a) { uint32_t v; asm volatile("ld.shared.u32 %0, [%1];" : "=r"(v) : "r"(a) : "memory"); return v; }
__device__ __forceinline__ void stsm4(uint32_t a, uint32_t x, uint32_t y, uint32_t z, uint32_t w) {
    asm volatile("stmatrix.sync.aligned.m8n8.x4.shared.b16 [%0], {%1, %2, %3, %4};" :: "r"(a), "r"(x), "r"(y), "r"(z), "r"(w) : "memory");
}
__device__ __forceinline__ void red4(float* p, float a, float b, float c, float d) {
    asm volatile("red.global.add.v4.f32 [%0], {%1, %2, %3, %4};" :: "l"(p), "f"(a), "f"(b), "f"(c), "f"(d) : "memory");
}
__device__ __forceinline__ void mma16816(float (&d)[4], uint32_t a0, uint32_t a1, uint32_t a2, uint32_t a3, uint32_t b0, uint32_t b1) {
    asm volatile("mma.sync.aligned.m16n8k16.row.col.f32.bf16.bf16.f32 {%0, %1, %2, %3}, {%4, %5, %6, %7}, {%8, %9}, {%0, %1, %2, %3};"
        : "+f"(d[0]), "+f"(d[1]), "+f"(d[2]), "+f"(d[3]) : "r"(a0), "r"(a1), "r"(a2), "r"(a3), "r"(b0), "r"(b1));
}
__device__ __forceinline__ float phi(float t) {
    const float e = ex2(t * LOG2E);
    return t > 0.f ? t + 1.000001f : e + 1e-6f;
}

__device__ __forceinline__ void mma_ss128(float (&d)[64], uint32_t da, uint32_t db) {
    asm volatile("{\n.reg .b64 a, b;\nmov.b64 a, {%64, 0x40000040};\nmov.b64 b, {%65, 0x40000040};\n"
        "wgmma.mma_async.sync.aligned.m64n128k16.f32.bf16.bf16 {%0, %1, %2, %3, %4, %5, %6, %7, %8, %9, %10, %11, %12, %13, %14, %15, %16, %17, %18, %19, %20, %21, %22, %23, %24, %25, %26, %27, %28, %29, %30, %31, %32, %33, %34, %35, %36, %37, %38, %39, %40, %41, %42, %43, %44, %45, %46, %47, %48, %49, %50, %51, %52, %53, %54, %55, %56, %57, %58, %59, %60, %61, %62, %63}, a, b, 1, 1, 1, 0, 1;\n}"
        : "+f"(d[0]), "+f"(d[1]), "+f"(d[2]), "+f"(d[3]), "+f"(d[4]), "+f"(d[5]), "+f"(d[6]), "+f"(d[7]), "+f"(d[8]), "+f"(d[9]), "+f"(d[10]), "+f"(d[11]), "+f"(d[12]), "+f"(d[13]), "+f"(d[14]), "+f"(d[15]), "+f"(d[16]), "+f"(d[17]), "+f"(d[18]), "+f"(d[19]), "+f"(d[20]), "+f"(d[21]), "+f"(d[22]), "+f"(d[23]), "+f"(d[24]), "+f"(d[25]), "+f"(d[26]), "+f"(d[27]), "+f"(d[28]), "+f"(d[29]), "+f"(d[30]), "+f"(d[31]), "+f"(d[32]), "+f"(d[33]), "+f"(d[34]), "+f"(d[35]), "+f"(d[36]), "+f"(d[37]), "+f"(d[38]), "+f"(d[39]), "+f"(d[40]), "+f"(d[41]), "+f"(d[42]), "+f"(d[43]), "+f"(d[44]), "+f"(d[45]), "+f"(d[46]), "+f"(d[47]), "+f"(d[48]), "+f"(d[49]), "+f"(d[50]), "+f"(d[51]), "+f"(d[52]), "+f"(d[53]), "+f"(d[54]), "+f"(d[55]), "+f"(d[56]), "+f"(d[57]), "+f"(d[58]), "+f"(d[59]), "+f"(d[60]), "+f"(d[61]), "+f"(d[62]), "+f"(d[63])
        : "r"(da), "r"(db));
}
__device__ __forceinline__ void mma_rs128(float (&d)[64], uint32_t a0, uint32_t a1, uint32_t a2, uint32_t a3, uint32_t db) {
    asm volatile("{\n.reg .b64 b;\nmov.b64 b, {%68, 0x40000040};\n"
        "wgmma.mma_async.sync.aligned.m64n128k16.f32.bf16.bf16 {%0, %1, %2, %3, %4, %5, %6, %7, %8, %9, %10, %11, %12, %13, %14, %15, %16, %17, %18, %19, %20, %21, %22, %23, %24, %25, %26, %27, %28, %29, %30, %31, %32, %33, %34, %35, %36, %37, %38, %39, %40, %41, %42, %43, %44, %45, %46, %47, %48, %49, %50, %51, %52, %53, %54, %55, %56, %57, %58, %59, %60, %61, %62, %63}, {%64, %65, %66, %67}, b, 1, 1, 1, 1;\n}"
        : "+f"(d[0]), "+f"(d[1]), "+f"(d[2]), "+f"(d[3]), "+f"(d[4]), "+f"(d[5]), "+f"(d[6]), "+f"(d[7]), "+f"(d[8]), "+f"(d[9]), "+f"(d[10]), "+f"(d[11]), "+f"(d[12]), "+f"(d[13]), "+f"(d[14]), "+f"(d[15]), "+f"(d[16]), "+f"(d[17]), "+f"(d[18]), "+f"(d[19]), "+f"(d[20]), "+f"(d[21]), "+f"(d[22]), "+f"(d[23]), "+f"(d[24]), "+f"(d[25]), "+f"(d[26]), "+f"(d[27]), "+f"(d[28]), "+f"(d[29]), "+f"(d[30]), "+f"(d[31]), "+f"(d[32]), "+f"(d[33]), "+f"(d[34]), "+f"(d[35]), "+f"(d[36]), "+f"(d[37]), "+f"(d[38]), "+f"(d[39]), "+f"(d[40]), "+f"(d[41]), "+f"(d[42]), "+f"(d[43]), "+f"(d[44]), "+f"(d[45]), "+f"(d[46]), "+f"(d[47]), "+f"(d[48]), "+f"(d[49]), "+f"(d[50]), "+f"(d[51]), "+f"(d[52]), "+f"(d[53]), "+f"(d[54]), "+f"(d[55]), "+f"(d[56]), "+f"(d[57]), "+f"(d[58]), "+f"(d[59]), "+f"(d[60]), "+f"(d[61]), "+f"(d[62]), "+f"(d[63])
        : "r"(a0), "r"(a1), "r"(a2), "r"(a3), "r"(db));
}
__device__ __forceinline__ void mma_rs128z(float (&d)[64], uint32_t a0, uint32_t a1, uint32_t a2, uint32_t a3, uint32_t db) {
    asm volatile("{\n.reg .b64 b;\nmov.b64 b, {%68, 0x40000040};\n"
        "wgmma.mma_async.sync.aligned.m64n128k16.f32.bf16.bf16 {%0, %1, %2, %3, %4, %5, %6, %7, %8, %9, %10, %11, %12, %13, %14, %15, %16, %17, %18, %19, %20, %21, %22, %23, %24, %25, %26, %27, %28, %29, %30, %31, %32, %33, %34, %35, %36, %37, %38, %39, %40, %41, %42, %43, %44, %45, %46, %47, %48, %49, %50, %51, %52, %53, %54, %55, %56, %57, %58, %59, %60, %61, %62, %63}, {%64, %65, %66, %67}, b, 0, 1, 1, 1;\n}"
        : "=f"(d[0]), "=f"(d[1]), "=f"(d[2]), "=f"(d[3]), "=f"(d[4]), "=f"(d[5]), "=f"(d[6]), "=f"(d[7]), "=f"(d[8]), "=f"(d[9]), "=f"(d[10]), "=f"(d[11]), "=f"(d[12]), "=f"(d[13]), "=f"(d[14]), "=f"(d[15]), "=f"(d[16]), "=f"(d[17]), "=f"(d[18]), "=f"(d[19]), "=f"(d[20]), "=f"(d[21]), "=f"(d[22]), "=f"(d[23]), "=f"(d[24]), "=f"(d[25]), "=f"(d[26]), "=f"(d[27]), "=f"(d[28]), "=f"(d[29]), "=f"(d[30]), "=f"(d[31]), "=f"(d[32]), "=f"(d[33]), "=f"(d[34]), "=f"(d[35]), "=f"(d[36]), "=f"(d[37]), "=f"(d[38]), "=f"(d[39]), "=f"(d[40]), "=f"(d[41]), "=f"(d[42]), "=f"(d[43]), "=f"(d[44]), "=f"(d[45]), "=f"(d[46]), "=f"(d[47]), "=f"(d[48]), "=f"(d[49]), "=f"(d[50]), "=f"(d[51]), "=f"(d[52]), "=f"(d[53]), "=f"(d[54]), "=f"(d[55]), "=f"(d[56]), "=f"(d[57]), "=f"(d[58]), "=f"(d[59]), "=f"(d[60]), "=f"(d[61]), "=f"(d[62]), "=f"(d[63])
        : "r"(a0), "r"(a1), "r"(a2), "r"(a3), "r"(db));
}
__device__ __forceinline__ void mma_rs128t(float (&d)[64], uint32_t a0, uint32_t a1, uint32_t a2, uint32_t a3, uint32_t db) {
    asm volatile("{\n.reg .b64 b;\nmov.b64 b, {%68, 0x40000040};\n"
        "wgmma.mma_async.sync.aligned.m64n128k16.f32.bf16.bf16 {%0, %1, %2, %3, %4, %5, %6, %7, %8, %9, %10, %11, %12, %13, %14, %15, %16, %17, %18, %19, %20, %21, %22, %23, %24, %25, %26, %27, %28, %29, %30, %31, %32, %33, %34, %35, %36, %37, %38, %39, %40, %41, %42, %43, %44, %45, %46, %47, %48, %49, %50, %51, %52, %53, %54, %55, %56, %57, %58, %59, %60, %61, %62, %63}, {%64, %65, %66, %67}, b, 1, 1, 1, 0;\n}"
        : "+f"(d[0]), "+f"(d[1]), "+f"(d[2]), "+f"(d[3]), "+f"(d[4]), "+f"(d[5]), "+f"(d[6]), "+f"(d[7]), "+f"(d[8]), "+f"(d[9]), "+f"(d[10]), "+f"(d[11]), "+f"(d[12]), "+f"(d[13]), "+f"(d[14]), "+f"(d[15]), "+f"(d[16]), "+f"(d[17]), "+f"(d[18]), "+f"(d[19]), "+f"(d[20]), "+f"(d[21]), "+f"(d[22]), "+f"(d[23]), "+f"(d[24]), "+f"(d[25]), "+f"(d[26]), "+f"(d[27]), "+f"(d[28]), "+f"(d[29]), "+f"(d[30]), "+f"(d[31]), "+f"(d[32]), "+f"(d[33]), "+f"(d[34]), "+f"(d[35]), "+f"(d[36]), "+f"(d[37]), "+f"(d[38]), "+f"(d[39]), "+f"(d[40]), "+f"(d[41]), "+f"(d[42]), "+f"(d[43]), "+f"(d[44]), "+f"(d[45]), "+f"(d[46]), "+f"(d[47]), "+f"(d[48]), "+f"(d[49]), "+f"(d[50]), "+f"(d[51]), "+f"(d[52]), "+f"(d[53]), "+f"(d[54]), "+f"(d[55]), "+f"(d[56]), "+f"(d[57]), "+f"(d[58]), "+f"(d[59]), "+f"(d[60]), "+f"(d[61]), "+f"(d[62]), "+f"(d[63])
        : "r"(a0), "r"(a1), "r"(a2), "r"(a3), "r"(db));
}
__device__ __forceinline__ void mma_rs128tz(float (&d)[64], uint32_t a0, uint32_t a1, uint32_t a2, uint32_t a3, uint32_t db) {
    asm volatile("{\n.reg .b64 b;\nmov.b64 b, {%68, 0x40000040};\n"
        "wgmma.mma_async.sync.aligned.m64n128k16.f32.bf16.bf16 {%0, %1, %2, %3, %4, %5, %6, %7, %8, %9, %10, %11, %12, %13, %14, %15, %16, %17, %18, %19, %20, %21, %22, %23, %24, %25, %26, %27, %28, %29, %30, %31, %32, %33, %34, %35, %36, %37, %38, %39, %40, %41, %42, %43, %44, %45, %46, %47, %48, %49, %50, %51, %52, %53, %54, %55, %56, %57, %58, %59, %60, %61, %62, %63}, {%64, %65, %66, %67}, b, 0, 1, 1, 0;\n}"
        : "=f"(d[0]), "=f"(d[1]), "=f"(d[2]), "=f"(d[3]), "=f"(d[4]), "=f"(d[5]), "=f"(d[6]), "=f"(d[7]), "=f"(d[8]), "=f"(d[9]), "=f"(d[10]), "=f"(d[11]), "=f"(d[12]), "=f"(d[13]), "=f"(d[14]), "=f"(d[15]), "=f"(d[16]), "=f"(d[17]), "=f"(d[18]), "=f"(d[19]), "=f"(d[20]), "=f"(d[21]), "=f"(d[22]), "=f"(d[23]), "=f"(d[24]), "=f"(d[25]), "=f"(d[26]), "=f"(d[27]), "=f"(d[28]), "=f"(d[29]), "=f"(d[30]), "=f"(d[31]), "=f"(d[32]), "=f"(d[33]), "=f"(d[34]), "=f"(d[35]), "=f"(d[36]), "=f"(d[37]), "=f"(d[38]), "=f"(d[39]), "=f"(d[40]), "=f"(d[41]), "=f"(d[42]), "=f"(d[43]), "=f"(d[44]), "=f"(d[45]), "=f"(d[46]), "=f"(d[47]), "=f"(d[48]), "=f"(d[49]), "=f"(d[50]), "=f"(d[51]), "=f"(d[52]), "=f"(d[53]), "=f"(d[54]), "=f"(d[55]), "=f"(d[56]), "=f"(d[57]), "=f"(d[58]), "=f"(d[59]), "=f"(d[60]), "=f"(d[61]), "=f"(d[62]), "=f"(d[63])
        : "r"(a0), "r"(a1), "r"(a2), "r"(a3), "r"(db));
}
__device__ __forceinline__ void mma_ss32(float (&d)[16], uint32_t da, uint32_t db) {
    asm volatile("{\n.reg .b64 a, b;\nmov.b64 a, {%16, 0x40000040};\nmov.b64 b, {%17, 0x80000020};\n"
        "wgmma.mma_async.sync.aligned.m64n32k16.f32.bf16.bf16 {%0, %1, %2, %3, %4, %5, %6, %7, %8, %9, %10, %11, %12, %13, %14, %15}, a, b, 1, 1, 1, 0, 1;\n}"
        : "+f"(d[0]), "+f"(d[1]), "+f"(d[2]), "+f"(d[3]), "+f"(d[4]), "+f"(d[5]), "+f"(d[6]), "+f"(d[7]), "+f"(d[8]), "+f"(d[9]), "+f"(d[10]), "+f"(d[11]), "+f"(d[12]), "+f"(d[13]), "+f"(d[14]), "+f"(d[15])
        : "r"(da), "r"(db));
}
__device__ __forceinline__ void mma_qk0(float (&d)[32], uint32_t a0, uint32_t a1, uint32_t a2, uint32_t a3, uint32_t db) {
    asm volatile("{\n.reg .b64 b;\nmov.b64 b, {%36, 0x80000020};\n"
        "wgmma.mma_async.sync.aligned.m64n64k16.f32.bf16.bf16 {%0, %1, %2, %3, %4, %5, %6, %7, %8, %9, %10, %11, %12, %13, %14, %15, %16, %17, %18, %19, %20, %21, %22, %23, %24, %25, %26, %27, %28, %29, %30, %31}, {%32, %33, %34, %35}, b, 0, 1, 1, 0;\n}"
        : "=f"(d[0]), "=f"(d[1]), "=f"(d[2]), "=f"(d[3]), "=f"(d[4]), "=f"(d[5]), "=f"(d[6]), "=f"(d[7]), "=f"(d[8]), "=f"(d[9]), "=f"(d[10]), "=f"(d[11]), "=f"(d[12]), "=f"(d[13]), "=f"(d[14]), "=f"(d[15]), "=f"(d[16]), "=f"(d[17]), "=f"(d[18]), "=f"(d[19]), "=f"(d[20]), "=f"(d[21]), "=f"(d[22]), "=f"(d[23]), "=f"(d[24]), "=f"(d[25]), "=f"(d[26]), "=f"(d[27]), "=f"(d[28]), "=f"(d[29]), "=f"(d[30]), "=f"(d[31])
        : "r"(a0), "r"(a1), "r"(a2), "r"(a3), "r"(db));
}
__device__ __forceinline__ void mma_qk1(float (&d)[32], uint32_t a0, uint32_t a1, uint32_t a2, uint32_t a3, uint32_t db) {
    asm volatile("{\n.reg .b64 b;\nmov.b64 b, {%36, 0x80000020};\n"
        "wgmma.mma_async.sync.aligned.m64n64k16.f32.bf16.bf16 {%0, %1, %2, %3, %4, %5, %6, %7, %8, %9, %10, %11, %12, %13, %14, %15, %16, %17, %18, %19, %20, %21, %22, %23, %24, %25, %26, %27, %28, %29, %30, %31}, {%32, %33, %34, %35}, b, 1, 1, 1, 0;\n}"
        : "+f"(d[0]), "+f"(d[1]), "+f"(d[2]), "+f"(d[3]), "+f"(d[4]), "+f"(d[5]), "+f"(d[6]), "+f"(d[7]), "+f"(d[8]), "+f"(d[9]), "+f"(d[10]), "+f"(d[11]), "+f"(d[12]), "+f"(d[13]), "+f"(d[14]), "+f"(d[15]), "+f"(d[16]), "+f"(d[17]), "+f"(d[18]), "+f"(d[19]), "+f"(d[20]), "+f"(d[21]), "+f"(d[22]), "+f"(d[23]), "+f"(d[24]), "+f"(d[25]), "+f"(d[26]), "+f"(d[27]), "+f"(d[28]), "+f"(d[29]), "+f"(d[30]), "+f"(d[31])
        : "r"(a0), "r"(a1), "r"(a2), "r"(a3), "r"(db));
}
__device__ __forceinline__ void mma_pv(float (&d)[20], uint32_t a0, uint32_t a1, uint32_t a2, uint32_t a3, uint32_t db) {
    asm volatile("{\n.reg .b64 b;\nmov.b64 b, {%24, 0x80000020};\n"
        "wgmma.mma_async.sync.aligned.m64n40k16.f32.bf16.bf16 {%0, %1, %2, %3, %4, %5, %6, %7, %8, %9, %10, %11, %12, %13, %14, %15, %16, %17, %18, %19}, {%20, %21, %22, %23}, b, 1, 1, 1, 1;\n}"
        : "+f"(d[0]), "+f"(d[1]), "+f"(d[2]), "+f"(d[3]), "+f"(d[4]), "+f"(d[5]), "+f"(d[6]), "+f"(d[7]), "+f"(d[8]), "+f"(d[9]), "+f"(d[10]), "+f"(d[11]), "+f"(d[12]), "+f"(d[13]), "+f"(d[14]), "+f"(d[15]), "+f"(d[16]), "+f"(d[17]), "+f"(d[18]), "+f"(d[19])
        : "r"(a0), "r"(a1), "r"(a2), "r"(a3), "r"(db));
}
__device__ __forceinline__ void mma_pvp(float (&d)[20], uint32_t a0, uint32_t a1, uint32_t a2, uint32_t a3, uint32_t db, uint32_t acc) {
    asm volatile("{\n.reg .b64 b;\n.reg .pred p;\nsetp.ne.u32 p, %25, 0;\nmov.b64 b, {%24, 0x80000020};\n"
        "wgmma.mma_async.sync.aligned.m64n40k16.f32.bf16.bf16 {%0, %1, %2, %3, %4, %5, %6, %7, %8, %9, %10, %11, %12, %13, %14, %15, %16, %17, %18, %19}, {%20, %21, %22, %23}, b, p, 1, 1, 1;\n}"
        : "+f"(d[0]), "+f"(d[1]), "+f"(d[2]), "+f"(d[3]), "+f"(d[4]), "+f"(d[5]), "+f"(d[6]), "+f"(d[7]), "+f"(d[8]), "+f"(d[9]), "+f"(d[10]), "+f"(d[11]), "+f"(d[12]), "+f"(d[13]), "+f"(d[14]), "+f"(d[15]), "+f"(d[16]), "+f"(d[17]), "+f"(d[18]), "+f"(d[19])
        : "r"(a0), "r"(a1), "r"(a2), "r"(a3), "r"(db), "r"(acc));
}
__device__ __forceinline__ void mma_kv0(float (&d)[32], uint32_t a0, uint32_t a1, uint32_t a2, uint32_t a3, uint32_t db) {
    asm volatile("{\n.reg .b64 b;\nmov.b64 b, {%36, 0x40000040};\n"
        "wgmma.mma_async.sync.aligned.m64n64k16.f32.bf16.bf16 {%0, %1, %2, %3, %4, %5, %6, %7, %8, %9, %10, %11, %12, %13, %14, %15, %16, %17, %18, %19, %20, %21, %22, %23, %24, %25, %26, %27, %28, %29, %30, %31}, {%32, %33, %34, %35}, b, 0, 1, 1, 1;\n}"
        : "=f"(d[0]), "=f"(d[1]), "=f"(d[2]), "=f"(d[3]), "=f"(d[4]), "=f"(d[5]), "=f"(d[6]), "=f"(d[7]), "=f"(d[8]), "=f"(d[9]), "=f"(d[10]), "=f"(d[11]), "=f"(d[12]), "=f"(d[13]), "=f"(d[14]), "=f"(d[15]), "=f"(d[16]), "=f"(d[17]), "=f"(d[18]), "=f"(d[19]), "=f"(d[20]), "=f"(d[21]), "=f"(d[22]), "=f"(d[23]), "=f"(d[24]), "=f"(d[25]), "=f"(d[26]), "=f"(d[27]), "=f"(d[28]), "=f"(d[29]), "=f"(d[30]), "=f"(d[31])
        : "r"(a0), "r"(a1), "r"(a2), "r"(a3), "r"(db));
}
__device__ __forceinline__ void mma_kv1(float (&d)[32], uint32_t a0, uint32_t a1, uint32_t a2, uint32_t a3, uint32_t db) {
    asm volatile("{\n.reg .b64 b;\nmov.b64 b, {%36, 0x40000040};\n"
        "wgmma.mma_async.sync.aligned.m64n64k16.f32.bf16.bf16 {%0, %1, %2, %3, %4, %5, %6, %7, %8, %9, %10, %11, %12, %13, %14, %15, %16, %17, %18, %19, %20, %21, %22, %23, %24, %25, %26, %27, %28, %29, %30, %31}, {%32, %33, %34, %35}, b, 1, 1, 1, 1;\n}"
        : "+f"(d[0]), "+f"(d[1]), "+f"(d[2]), "+f"(d[3]), "+f"(d[4]), "+f"(d[5]), "+f"(d[6]), "+f"(d[7]), "+f"(d[8]), "+f"(d[9]), "+f"(d[10]), "+f"(d[11]), "+f"(d[12]), "+f"(d[13]), "+f"(d[14]), "+f"(d[15]), "+f"(d[16]), "+f"(d[17]), "+f"(d[18]), "+f"(d[19]), "+f"(d[20]), "+f"(d[21]), "+f"(d[22]), "+f"(d[23]), "+f"(d[24]), "+f"(d[25]), "+f"(d[26]), "+f"(d[27]), "+f"(d[28]), "+f"(d[29]), "+f"(d[30]), "+f"(d[31])
        : "r"(a0), "r"(a1), "r"(a2), "r"(a3), "r"(db));
}
__device__ __forceinline__ void mma_num0(float (&d)[20], uint32_t a0, uint32_t a1, uint32_t a2, uint32_t a3, uint32_t db) {
    asm volatile("{\n.reg .b64 b;\nmov.b64 b, {%24, 0x20};\n"
        "wgmma.mma_async.sync.aligned.m64n40k16.f32.bf16.bf16 {%0, %1, %2, %3, %4, %5, %6, %7, %8, %9, %10, %11, %12, %13, %14, %15, %16, %17, %18, %19}, {%20, %21, %22, %23}, b, 0, 1, 1, 0;\n}"
        : "=f"(d[0]), "=f"(d[1]), "=f"(d[2]), "=f"(d[3]), "=f"(d[4]), "=f"(d[5]), "=f"(d[6]), "=f"(d[7]), "=f"(d[8]), "=f"(d[9]), "=f"(d[10]), "=f"(d[11]), "=f"(d[12]), "=f"(d[13]), "=f"(d[14]), "=f"(d[15]), "=f"(d[16]), "=f"(d[17]), "=f"(d[18]), "=f"(d[19])
        : "r"(a0), "r"(a1), "r"(a2), "r"(a3), "r"(db));
}
__device__ __forceinline__ void mma_num1(float (&d)[20], uint32_t a0, uint32_t a1, uint32_t a2, uint32_t a3, uint32_t db) {
    asm volatile("{\n.reg .b64 b;\nmov.b64 b, {%24, 0x20};\n"
        "wgmma.mma_async.sync.aligned.m64n40k16.f32.bf16.bf16 {%0, %1, %2, %3, %4, %5, %6, %7, %8, %9, %10, %11, %12, %13, %14, %15, %16, %17, %18, %19}, {%20, %21, %22, %23}, b, 1, 1, 1, 0;\n}"
        : "+f"(d[0]), "+f"(d[1]), "+f"(d[2]), "+f"(d[3]), "+f"(d[4]), "+f"(d[5]), "+f"(d[6]), "+f"(d[7]), "+f"(d[8]), "+f"(d[9]), "+f"(d[10]), "+f"(d[11]), "+f"(d[12]), "+f"(d[13]), "+f"(d[14]), "+f"(d[15]), "+f"(d[16]), "+f"(d[17]), "+f"(d[18]), "+f"(d[19])
        : "r"(a0), "r"(a1), "r"(a2), "r"(a3), "r"(db));
}

__device__ __forceinline__ void issue_qk(float (&S)[32], const uint32_t (&q)[8], uint32_t dk) {
    mma_qk0(S, q[0], q[1], q[2], q[3], dk);
    mma_qk1(S, q[4], q[5], q[6], q[7], dk + 2);
}
constexpr uint32_t VSTEP = 1u - 65536u;
__device__ __forceinline__ void issue_pv(float (&O)[20], const uint32_t (&P)[16], uint32_t dv) {
#pragma unroll
    for (int k = 0; k < 4; k++) mma_pv(O, P[4 * k], P[4 * k + 1], P[4 * k + 2], P[4 * k + 3], dv + k * 64 * VSTEP);
}
__device__ __forceinline__ void issue_step(float (&S)[32], const uint32_t (&q)[8], float (&O)[20], const uint32_t (&P)[16], uint32_t dk, uint32_t dv,
                                           uint32_t keep = 1) {
    wg_fence();
    mma_pvp(O, P[0], P[1], P[2], P[3], dv, keep);
    mma_qk0(S, q[0], q[1], q[2], q[3], dk);
    mma_pv(O, P[4], P[5], P[6], P[7], dv + 64 * VSTEP);
    mma_qk1(S, q[4], q[5], q[6], q[7], dk + 2);
    mma_pv(O, P[8], P[9], P[10], P[11], dv + 128 * VSTEP);
    mma_pv(O, P[12], P[13], P[14], P[15], dv + 192 * VSTEP);
    wg_commit();
}
__device__ __forceinline__ void exp_tile(const float (&S)[32], uint32_t (&P)[16]) {
#pragma unroll
    for (int i = 0; i < 16; i++) P[i] = pack(ex2(S[2 * i]), ex2(S[2 * i + 1]));
    pin(P);
}
template <int N>
__device__ __forceinline__ void store_o(const float (&O)[N], float l0, float l1, __nv_bfloat16* dst, uint4& v0, uint4& v1) {
    float r0 = rcp(l0), r1 = rcp(l1);
    v0 = make_uint4(pack(O[0] * r0, O[1] * r0), pack(O[4] * r0, O[5] * r0), pack(O[8] * r0, O[9] * r0), pack(O[12] * r0, O[13] * r0));
    v1 = make_uint4(pack(O[2] * r1, O[3] * r1), pack(O[6] * r1, O[7] * r1), pack(O[10] * r1, O[11] * r1), pack(O[14] * r1, O[15] * r1));
    *reinterpret_cast<uint4*>(dst) = v0;
    *reinterpret_cast<uint4*>(dst + 8 * 1024) = v1;
}
__device__ __forceinline__ bool finish_pass(const float (&O)[20], __nv_bfloat16* dst, uint4& v0, uint4& v1) {
    const float l0 = O[16], l1 = O[18];
    store_o(O, l0, l1, dst, v0, v1);
    float sa = 0.f, sb = 0.f;
#pragma unroll
    for (int i = 0; i < 16; i += 4) { sa += fabsf(O[i]) + fabsf(O[i + 1]); sb += fabsf(O[i + 2]) + fabsf(O[i + 3]); }
    const float lo = 9.313225746154785e-10f  , hi = 2.81474976710656e14f  ;
    const bool ok = l0 >= lo && l0 <= hi && l1 >= lo && l1 <= hi && sa + sb <= 3.0e38f;
    const bool all = __all_sync(0xffffffffu, ok);
    __syncwarp();
    return all;
}
__device__ __forceinline__ float rbf(float x) { return __uint_as_float(pack(0.f, x)); }
__device__ __forceinline__ void slow_pass(const uint32_t (&q)[8], __nv_bfloat16* dst, uint4& v0, uint4& v1) {
    const int lane = threadIdx.x & 31, g = lane >> 2, t = lane & 3;
    const unsigned short* V = reinterpret_cast<const unsigned short*>(g_kv) + 2048 * 32;
    float o[4][4], m0 = -3.0e38f, m1 = -3.0e38f, l0 = 0.f, l1 = 0.f;
#pragma unroll
    for (int c = 0; c < 4; c++) { o[c][0] = o[c][1] = o[c][2] = o[c][3] = 0.f; }
#pragma unroll 1
    for (int k0 = 0; k0 < 2048; k0 += 16) {
        float s[2][4];
#pragma unroll
        for (int nt = 0; nt < 2; nt++) {
            s[nt][0] = s[nt][1] = s[nt][2] = s[nt][3] = 0.f;
            const uint4 kf = __ldcg(g_q + K0 + (k0 + 8 * nt + g) * 4 + t);
            mma16816(s[nt], q[0], q[1], q[2], q[3], kf.x, kf.y);
            mma16816(s[nt], q[4], q[5], q[6], q[7], kf.z, kf.w);
#pragma unroll
            for (int i = 0; i < 4; i++) s[nt][i] = rbf(rbf(s[nt][i]) * 0.17677669529663687f);
        }
        float a0 = fmaxf(fmaxf(s[0][0], s[0][1]), fmaxf(s[1][0], s[1][1]));
        float a1 = fmaxf(fmaxf(s[0][2], s[0][3]), fmaxf(s[1][2], s[1][3]));
        a0 = fmaxf(a0, __shfl_xor_sync(0xffffffffu, a0, 1)); a1 = fmaxf(a1, __shfl_xor_sync(0xffffffffu, a1, 1));
        a0 = fmaxf(a0, __shfl_xor_sync(0xffffffffu, a0, 2)); a1 = fmaxf(a1, __shfl_xor_sync(0xffffffffu, a1, 2));
        float n0 = fmaxf(m0, a0), n1 = fmaxf(m1, a1);
        float c0 = ex2((m0 - n0) * LOG2E), c1 = ex2((m1 - n1) * LOG2E);
        m0 = n0; m1 = n1;
        float e[2][4];
#pragma unroll
        for (int nt = 0; nt < 2; nt++) {
            e[nt][0] = ex2((s[nt][0] - m0) * LOG2E); e[nt][1] = ex2((s[nt][1] - m0) * LOG2E);
            e[nt][2] = ex2((s[nt][2] - m1) * LOG2E); e[nt][3] = ex2((s[nt][3] - m1) * LOG2E);
        }
        l0 = l0 * c0 + ((e[0][0] + e[0][1]) + (e[1][0] + e[1][1]));
        l1 = l1 * c1 + ((e[0][2] + e[0][3]) + (e[1][2] + e[1][3]));
        uint32_t p0 = pack(e[0][0], e[0][1]), p1 = pack(e[0][2], e[0][3]), p2 = pack(e[1][0], e[1][1]), p3 = pack(e[1][2], e[1][3]);
#pragma unroll
        for (int c = 0; c < 4; c++) {
            o[c][0] *= c0; o[c][1] *= c0; o[c][2] *= c1; o[c][3] *= c1;
            const unsigned short* vr = V + (k0 + 2 * t) * 32 + 8 * (c ^ t) + g;
            uint32_t b0 = (uint32_t)__ldcg(vr) | ((uint32_t)__ldcg(vr + 32) << 16);
            uint32_t b1 = (uint32_t)__ldcg(vr + 256) | ((uint32_t)__ldcg(vr + 288) << 16);
            mma16816(o[c], p0, p1, p2, p3, b0, b1);
        }
    }
    l0 += __shfl_xor_sync(0xffffffffu, l0, 1); l1 += __shfl_xor_sync(0xffffffffu, l1, 1);
    l0 += __shfl_xor_sync(0xffffffffu, l0, 2); l1 += __shfl_xor_sync(0xffffffffu, l1, 2);
    float O[16];
#pragma unroll
    for (int c = 0; c < 4; c++) { O[4 * c] = o[c][0]; O[4 * c + 1] = o[c][1]; O[4 * c + 2] = o[c][2]; O[4 * c + 3] = o[c][3]; }
    store_o(O, l0, l1, dst, v0, v1);
    __syncwarp();
}

template <bool TRANS>
__device__ __forceinline__ void load_a(uint32_t (&f)[8], uint32_t la, int ks) {
#pragma unroll
    for (int h = 0; h < 2; h++) {
        if (TRANS)
            asm volatile("ldmatrix.sync.aligned.m8n8.x4.trans.shared.b16 {%0, %1, %2, %3}, [%4];"
                : "=r"(f[4 * h]), "=r"(f[4 * h + 1]), "=r"(f[4 * h + 2]), "=r"(f[4 * h + 3]) : "r"(la + h * 8192 + ks * 2048) : "memory");
        else
            asm volatile("ldmatrix.sync.aligned.m8n8.x4.shared.b16 {%0, %1, %2, %3}, [%4];"
                : "=r"(f[4 * h]), "=r"(f[4 * h + 1]), "=r"(f[4 * h + 2]), "=r"(f[4 * h + 3]) : "r"((la ^ (ks << 5)) + h * 8192) : "memory");
    }
}
template <bool TRANS, bool ZERO>
__device__ __forceinline__ void paced_step(float (&a0)[64], float (&a1)[64], const uint32_t (&f)[8], uint32_t db) {
    wg_fence();
    if (ZERO) {
        if (TRANS) { mma_rs128tz(a0, f[0], f[1], f[2], f[3], db); mma_rs128tz(a1, f[4], f[5], f[6], f[7], db); }
        else { mma_rs128z(a0, f[0], f[1], f[2], f[3], db); mma_rs128z(a1, f[4], f[5], f[6], f[7], db); }
    } else {
        if (TRANS) { mma_rs128t(a0, f[0], f[1], f[2], f[3], db); mma_rs128t(a1, f[4], f[5], f[6], f[7], db); }
        else { mma_rs128(a0, f[0], f[1], f[2], f[3], db); mma_rs128(a1, f[4], f[5], f[6], f[7], db); }
    }
    wg_commit();
}
template <bool TRANS, bool FIRST>
__device__ __forceinline__ void paced_block(float (&a0)[64], float (&a1)[64], uint32_t (&fa)[8], uint32_t sb, int kb, int nkb, uint32_t la,
                                            uint32_t rempty, bool relp, uint32_t kw, float& z0, float& z1, bool hold) {
    const int s = kb & (NS - 1);
    const uint32_t db = (TRANS ? mkdesc(0, 16) : mkdesc(OFF_B, BLK)) + s * 1024;
    uint32_t fb[8];
#pragma unroll
    for (int ks = 0; ks < 4; ks++) {
        const uint32_t a = (kw ^ ((ks & 1) << 6)) + kb * 2048 + ks * 512;
        uint32_t r = 0;
        if (TRANS) r = lds32(a);
        if (ks & 1) paced_step<TRANS, false>(a0, a1, fb, db + ks * (TRANS ? 2 : 128));
        else if (FIRST && ks == 0) paced_step<TRANS, true>(a0, a1, fa, db);
        else paced_step<TRANS, false>(a0, a1, fa, db + ks * (TRANS ? 2 : 128));
        if (ks < 3) {
            if (ks & 1) load_a<TRANS>(fa, la + s * 16384, ks + 1); else load_a<TRANS>(fb, la + s * 16384, ks + 1);
        } else {
            const int nb = kb + 1;
            if (nb < nkb) mbar_wait(sb + OFF_BAR + B_FULL + 8 * (nb & (NS - 1)), (nb / NS) & 1);
            load_a<TRANS>(fa, la + (nb & (NS - 1)) * 16384, 0);
        }
        if (TRANS) {
            const float p0 = phi(__uint_as_float(r << 16)), p1 = phi(__uint_as_float(r & 0xFFFF0000u));
            z0 += p0; z1 += p1;
            asm volatile("st.shared.u32 [%0], %1;" :: "r"(a), "r"(pack(p0, p1)) : "memory");
        }
        wg_wait<0>();
    }
    if (FIRST && !TRANS && hold) { mbar_wait(sb + OFF_BAR + B_FULL + 16, 0); mbar_wait(sb + OFF_BAR + B_FULL + 24, 0); }
    mbar_arrive_cl(rempty + 8 * s, 2, relp);
}
template <bool TRANS>
__device__ __forceinline__ void gemm_paced(float (&a0)[64], float (&a1)[64], uint32_t sb, int nkb, uint32_t rempty, bool relp, float* zdst, bool hold) {
    const int lane = threadIdx.x & 31, wq = (threadIdx.x >> 5) & 3;
    const uint32_t kw = sb + OFF_STG + wq * 128 + (((lane >> 2) ^ wq) << 4) + (lane & 3) * 4;
    const uint32_t la = TRANS ? sb + OFF_B + ((lane & 7) + (lane >> 4) * 8) * 128 + (((2 * wq + ((lane >> 3) & 1)) ^ (lane & 7)) << 4)
                              : sb + (wq * 16 + (lane & 15)) * 128 + (((lane >> 4) ^ (lane & 7)) << 4);
    float z0 = 0.f, z1 = 0.f;
    uint32_t fa[8];
    mbar_wait(sb + OFF_BAR + B_FULL, 0);
    load_a<TRANS>(fa, la, 0);
    paced_block<TRANS, true>(a0, a1, fa, sb, 0, nkb, la, rempty, relp, kw, z0, z1, hold);
    int kb = 1;
#pragma unroll 1
    do {
        paced_block<TRANS, false>(a0, a1, fa, sb, kb, nkb, la, rempty, relp, kw, z0, z1, hold);
        if (TRANS && (kb & 7) == 7) {
            asm volatile("red.global.add.v2.f32 [%0], {%1, %2};" :: "l"(zdst + (kb >> 3) * 2112), "f"(z0), "f"(z1) : "memory");
            z0 = z1 = 0.f;
        }
    } while (++kb < nkb);
    pin(a0); pin(a1);
}
template <int C0 = 0, int C1 = 16>
__device__ __forceinline__ void stage_tile(const float (&a)[64], uint32_t stg, int row0) {
    const int lane = threadIdx.x & 31;
    const int row = row0 + (lane & 7) + (lane & 8);
    const uint32_t base = stg + row * 128;
#pragma unroll
    for (int c = C0; c < C1; c += 2) {
        const int ch = c + (lane >> 4);
        stsm4(base + (c >> 3) * 16384 + (((ch & 7) ^ (lane & 7)) << 4),
              pack(a[4 * c], a[4 * c + 1]), pack(a[4 * c + 2], a[4 * c + 3]), pack(a[4 * c + 4], a[4 * c + 5]), pack(a[4 * c + 6], a[4 * c + 7]));
    }
}
__device__ __forceinline__ void frag_pack(const float (&a)[64], uint32_t (&pq)[32]) {
#pragma unroll
    for (int c = 0; c < 32; c++) pq[c] = pack(a[2 * c], a[2 * c + 1]);
    pin(pq);
}
__device__ __forceinline__ void issue_kv(float (&kv)[32], const uint32_t (&pk)[32], uint32_t vtile) {
    const uint32_t dv = mkdesc(vtile, 16);
    mma_kv0(kv, pk[0], pk[1], pk[2], pk[3], dv);
#pragma unroll
    for (int k = 1; k < 8; k++) mma_kv1(kv, pk[4 * k], pk[4 * k + 1], pk[4 * k + 2], pk[4 * k + 3], dv + k * 128);
}
__device__ __forceinline__ void red_kv(const float (&kv)[32], bool hi, float* r) {
    float v[16];
#pragma unroll
    for (int k = 0; k < 16; k++) v[k] = hi ? kv[16 + k] : kv[k];
    red4(r, v[0], v[1], v[4], v[5]); red4(r + 4, v[8], v[9], v[12], v[13]);
    red4(r + 256, v[2], v[3], v[6], v[7]); red4(r + 260, v[10], v[11], v[14], v[15]);
}
__device__ __forceinline__ void phi_head(const float* a, uint32_t (&pq)[8]) {
#pragma unroll
    for (int c = 0; c < 8; c++) pq[c] = pack(phi(a[2 * c]), phi(a[2 * c + 1]));
    pin(pq);
}
__device__ __forceinline__ void issue_num(float (&n)[20], const uint32_t (&pq)[8], uint32_t db) {
    wg_fence();
    mma_num0(n, pq[0], pq[1], pq[2], pq[3], db);
    mma_num1(n, pq[4], pq[5], pq[6], pq[7], db + 16);
    wg_commit();
}
__device__ __forceinline__ void lin_store(const float (&n)[20], int u, __nv_bfloat16* dst, uint32_t sa) {
    uint4 v0, v1;
    store_o(n, n[16] + 1e-6f, n[18] + 1e-6f, dst + (u >> 2) * 64 * 1024 + (u & 3) * 32, v0, v1);
    const uint32_t a = (sa ^ ((u & 1) << 6)) + (u >> 2) * 8192 + (u & 2) * 8192;
    sts128(a, v0.x, v0.y, v0.z, v0.w); sts128(a + 1024, v1.x, v1.y, v1.z, v1.w);
}
__device__ __forceinline__ void lin_out(const float (&a0)[64], const float (&a1)[64], uint32_t sb, __nv_bfloat16* dst, uint32_t sa) {
    const uint32_t db = mkdesc(OFF_STG, 128);
    float n0[20], n1[20];
    uint32_t p0[8], p1[8];
    phi_head(a0, p0); phi_head(a0 + 16, p1);
    force(p0); force(p1);
    mbar_wait(sb + OFF_BAR + B_PREP, 0);
    issue_num(n0, p0, db);
#pragma unroll
    for (int u = 0; u < 8; u += 2) {
        issue_num(n1, p1, db + ((u + 1) & 3) * 160);
        wg_wait<1>(); pin(n0);
        lin_store(n0, u, dst, sa);
        if (u < 6) {
            phi_head((u + 2 < 4 ? a0 : a1) + ((u + 2) & 3) * 16, p0);
            wg_bar(1);
            issue_num(n0, p0, db + ((u + 2) & 3) * 160);
            wg_wait<1>();
        } else {
            wg_wait<0>();
        }
        pin(n1);
        lin_store(n1, u + 1, dst, sa);
        if (u < 6) {
            phi_head((u + 3 < 4 ? a0 : a1) + ((u + 3) & 3) * 16, p1);
            wg_bar(1);
        }
    }
}

__device__ __forceinline__ void prep_operand(uint32_t sb, const float* src, int h0) {
    const int lane = threadIdx.x & 31, g = lane >> 2, t = lane & 3;
#pragma unroll 1
    for (int u = h0 * 4; u < h0 * 4 + 8; u++) {
        const float4* p = reinterpret_cast<const float4*>(src + (u >> 2) * 1056 + (u & 3) * 256) + lane * 2;
        const float4 x = __ldcg(p), y = __ldcg(p + 1);
        const uint32_t a = sb + OFF_STG + (u >> 2) * 2560 + (g >> 1) * 512 + ((u & 3) * 2 + (g & 1)) * 16 + t * 4;
        asm volatile("st.shared.u32 [%0], %1;\nst.shared.u32 [%0+128], %2;\nst.shared.u32 [%0+256], %3;\nst.shared.u32 [%0+384], %4;"
            :: "r"(a), "r"(pack(x.x, x.y)), "r"(pack(x.z, x.w)), "r"(pack(y.x, y.y)), "r"(pack(y.z, y.w)) : "memory");
    }
#pragma unroll 1
    for (int h = h0; h < h0 + 2; h++) {
        const float4* p = reinterpret_cast<const float4*>(src + h * 1056 + 1024) + t * 2;
        const float4 x = __ldcg(p), y = __ldcg(p + 1);
        sts128(sb + OFF_STG + h * 2560 + 2048 + t * 128 + g * 16, pack(x.x, x.y), pack(x.z, x.w), pack(y.x, y.y), pack(y.z, y.w));
    }
    fence_async_smem();
    __syncwarp();
    if (lane == 0) mbar_arrive(sb + OFF_BAR + B_PREP);
}

__device__ __forceinline__ void release_last(uint32_t sb, uint4 v0, uint4 v1, int nstage) {
    const int tid = threadIdx.x, lane = tid & 31;
    if (lane == 0) publish(g_flag + F_OB + 32 * (blockIdx.x >> 3) + 4 + (tid >> 7) * 4 + ((blockIdx.x & 7) >> 1));
    __syncwarp();
    mbar_wait(sb + OFF_BAR + B_KVE + 24, ((nstage + 1) >> 2) & 1);
    const uint32_t a = sb + OFF_OWN + ((tid >> 5) * 16 + (lane >> 2)) * 128 + ((((blockIdx.x & 1) * 4 + (lane & 3)) ^ (lane >> 2)) << 4);
#pragma unroll
    for (int r = 0; r < 2; r++) {
        const uint32_t ra = mapa(a, r), rb = mapa(sb + OFF_BAR + B_LAST + (tid >> 7) * 32, r);
        st_async4(ra, v0, rb); st_async4(ra + 1024, v1, rb);
    }
}

__device__ __forceinline__ void extra_cta(uint32_t sb, int sp) {
    const int tid = threadIdx.x, lane = tid & 31, tq = tid & 127;
    const int y = __shfl_sync(0xffffffffu, tid >> 7, 0);
    const uint32_t bar = sb + OFF_BAR;
    if (tid < 64) { sts128(sb + OFF_ONE + tid * 16, 0x3F803F80u, 0x3F803F80u, 0x3F803F80u, 0x3F803F80u); fence_async_smem(); }
    if (tid >= 480) {
        if (lane == 0) { mbar_init(bar, 1); asm volatile("fence.mbarrier_init.release.cluster;" ::: "memory"); mbar_expect(bar, 10 * 8192); }
        const unsigned epoch = *reinterpret_cast<volatile unsigned*>(g_flag + F_DONE) >> 7;
        const int blk = ((4 * sp + 14 + (lane >> 1)) & 15) + (lane & 1) * 16;
        uint32_t n = 0, t0 = 0;
        __nanosleep(4000);
        while (!__all_sync(0xffffffffu, lane >= 10 || (int)(ld_acq(g_flag + F_KV + blk * 32) - (epoch + 1) * 4) >= 0)) { __nanosleep(200); watchdog(n, t0); }
        __syncwarp();
        fence_async_gmem();
        if (lane < 10) bulk_ld(sb + lane * 8192, g_kv + blk * 4096, 8192, bar);
        mbar_wait_wd(bar, 0);
    }
    __syncthreads();
    mbar_wait(bar, 0);
    const unsigned* qflag = g_flag + F_Q3 + sp * 32;
    const unsigned qtarget = (*reinterpret_cast<volatile unsigned*>(g_flag + F_DONE) >> 7) + 1;
    poll(qflag + (y >> 1), qtarget);
    const uint32_t dk0 = mkdesc(0, 16), dv0 = mkdesc(8192, OFF_ONE - 8192);
    const uint4* qp = g_q + 6 * QS + sp * 32 * 256 + y * 128 + tq;
    uint4 qa = __ldcg(qp), qb = __ldcg(qp + QS);
    uint32_t q[8] = {qa.x, qa.y, qa.z, qa.w, qb.x, qb.y, qb.z, qb.w}, Pt[16];
    float S[32], O[20];
    zero(O); pin(q);
    wg_fence(); issue_qk(S, q, dk0); wg_commit(); wg_wait<0>(); pin(S);
#pragma unroll 1
    for (int u = y; u < 64; u += 4) {
        if (u < 60) qp += 512;
        const uint32_t o = (u >> 4) * 1024;
#pragma unroll 1
        for (int t = 0; t < 3; t++) {
            if (t == 2) {
                if (u < 4) poll(qflag + lane, qtarget);
                qa = __ldcg(qp); qb = __ldcg(qp + QS);
            }
            exp_tile(S, Pt);
            issue_step(S, q, O, Pt, dk0 + o + ((t + 1) >> 1) * 1024 + ((t + 1) & 1) * 256, dv0 + (o + (t >> 1) * 1024 + (t & 1) * 256) * VSTEP, t);
            wg_wait<0>(); pin(S); pin(O);
        }
        exp_tile(S, Pt);
        q[0] = qa.x; q[1] = qa.y; q[2] = qa.z; q[3] = qa.w; q[4] = qb.x; q[5] = qb.y; q[6] = qb.z; q[7] = qb.w;
        pin(q);
        issue_step(S, q, O, Pt, dk0 + ((u + 4) >> 4) * 1024, dv0 + (o + 1280) * VSTEP);
        wg_wait<0>(); pin(S); pin(O);
        float4* dst = g_part + (sp * 64 + u) * 640 + tq;
#pragma unroll
        for (int c = 0; c < 4; c++) dst[c * 128] = make_float4(O[4 * c], O[4 * c + 1], O[4 * c + 2], O[4 * c + 3]);
        *reinterpret_cast<float2*>(dst + 512) = make_float2(O[16], O[18]);
    }
    __syncthreads();
    if (tid == 0) publish(g_flag + F_PART + sp * 32);
}

__global__ void __cluster_dims__(2, 1, 1) __launch_bounds__(512, 1) fused_kernel(const __grid_constant__ Params P) {
    extern __shared__ __align__(1024) uint8_t smem_raw[];
    const uint32_t sb = (uint32_t)__cvta_generic_to_shared(smem_raw);
    if ((sb & 0x3FFFF) != SBASE) __trap();
    const uint32_t bar = sb + OFF_BAR;
    const int tid = threadIdx.x, lane = tid & 31;
    const int warp = __shfl_sync(0xffffffffu, tid >> 5, 0);
    const int bi = blockIdx.x >> 3, bj = blockIdx.x & 7, rank = blockIdx.x & 1;
    if (blockIdx.x >= 128) { extra_cta(sb, blockIdx.x - 128); return; }
    if (lane == 0) {
        const int grp = (warp + 6) & 15;
        mbar_init(bar + 24 * grp, (BC0 >> (4 * grp)) & 15);
        mbar_init(bar + 24 * grp + 8, (BC1 >> (4 * grp)) & 15);
        mbar_init(bar + 24 * grp + 16, (BC2 >> (4 * grp)) & 15);
        asm volatile("fence.mbarrier_init.release.cluster;" ::: "memory");
    }
    __syncwarp();
    asm volatile("barrier.cluster.arrive.relaxed.aligned;" ::: "memory");
    const int th = (bj >> 1) & 1;
    if (warp == 12 && elect()) {
        mbar_expect(bar + B_FULL, rank ? STAGE : STAGE - 8192);
        tma_ld_w(sb + OFF_B, &P.wq, 0, 0, bj * 2, bar + B_FULL);
#pragma unroll
        for (int c = 0; c < 2; c++) {
            mbar_expect(bar + B_XS - 8 * c, 8192);
            tma_ld(sb + OFF_KV + c * 8192, &P.xB, rank * 512 + c * 64, bi * 128 + th * 64, bar + B_XS - 8 * c);
        }
    }
    __syncwarp();
    asm volatile("barrier.cluster.wait.aligned;" ::: "memory");
    if (warp == 12 && elect()) {
#pragma unroll
        for (int s = 0; s < NS; s++) {
            const uint32_t fb = bar + B_FULL + 8 * s;
            const int kb = (s & 1) * 8 + (s >> 1);
            if (s) mbar_expect(fb, (s & 1) != rank ? STAGE : STAGE - 8192);
            if ((s & 1) != rank) tma_ld_mc(sb + s * 16384 + (th ^ 1) * 8192, &P.xB, kb * 64, bi * 128 + (th ^ 1) * 64, fb);
            if (s) tma_ld_w(sb + OFF_B + s * 16384, &P.wq, 0, 2 * kb, bj * 2, fb);
            if (s == NS - 1) {
#pragma unroll
                for (int c = 2; c < 4; c++) {
                    mbar_expect(bar + B_XS - 8 * c, 8192);
                    tma_ld(sb + OFF_KV + c * 8192, &P.xB, rank * 512 + c * 64, bi * 128 + th * 64, bar + B_XS - 8 * c);
                }
            }
        }
    }
    __syncwarp();

    if (warp < 8) {
        const int w = warp >> 2, wq = warp & 3;
        const uint32_t rbar = mapa(bar, wq & 1);
        uint32_t q[8], qn[8];
        if (wq < 2) {
            sts128(sb + OFF_ONE + (tid & 63) * 16, 0x3F803F80u, 0x3F803F80u, 0x3F803F80u, 0x3F803F80u);
            fence_async_smem();
        }
        asm volatile("setmaxnreg.inc.sync.aligned.u32 152;");
        if (w == 0) wg_bar(2); else wg_bar(3);
        const uint32_t d0 = mkdesc(OFF_KV, 16), dv0 = mkdesc(OFF_KV + 8192, OFF_ONE - OFF_KV - 8192);
        uint32_t ooff = (bi * 128 + w * 64 + wq * 16 + (lane >> 2)) * 1024 + bj * 32 + (lane & 3) * 8;
        asm volatile("" : "+r"(ooff));
        uint32_t fail = 0;
        const bool relp = lane == 0 && wq < 2;
        float S0[32], S1[32], O[20];
        uint32_t P0[16], P1[16];
        {
            float acc[64];
            zero(acc);
#pragma unroll 1
            for (int kb = 0; kb < 16; kb++) {
                const int s = kb & (NS - 1);
                if (kb == 7) mbar_wait(bar + B_KVMMA, 0);
                mbar_wait(bar + B_FULL + 8 * s, (kb / NS) & 1);
                const bool inplace = w == th && (kb & 1) == rank;
                if (inplace) mbar_wait(bar + B_XS - 8 * (kb >> 1), 0);
                const uint32_t dx = inplace ? mkdesc(OFF_KV, 16) + (kb >> 1) * 512 : mkdesc(0, 16) + s * 1024 + w * 512;
                const uint32_t dw = mkdesc(OFF_B, BLK) + s * 1024;
                wg_fence();
#pragma unroll
                for (int ks = 0; ks < 4; ks++) mma_ss128(acc, dx + ks * 2, dw + ks * 128);
                wg_commit();
                wg_wait<0>();
                mbar_arrive_cl(rbar + B_EMPTY + 8 * s, 1, relp);
            }
            if (tid == 0) mbar_arrive(bar + B_QDONE);
            pin(acc);
#pragma unroll
            for (int k = 0; k < 8; k++) q[k] = pack(acc[2 * k], acc[2 * k + 1]);
            pin(q);
            mbar_wait(bar + B_KVF, 0);
            wg_fence(); issue_qk(S0, q, d0); wg_commit();
#pragma unroll
            for (int k = 0; k < 8; k++) qn[k] = pack(acc[16 + 2 * k], acc[17 + 2 * k]);
#pragma unroll
            for (int h = 0; h < 4; h++) {
                const int b = 32 + 8 * h;
                g_q[(4 + h) * QS + blockIdx.x * 256 + tid] =
                    make_uint4(pack(acc[b], acc[b + 1]), pack(acc[b + 2], acc[b + 3]), pack(acc[b + 4], acc[b + 5]), pack(acc[b + 6], acc[b + 7]));
            }
            __syncwarp();
            if (lane == 0) mbar_arrive(bar + B_Q3);
            wg_wait<0>(); pin(S0); pin(qn);
        }
        zero(O);
        wg_fence(); issue_qk(S1, q, d0 + 256); wg_commit();
        exp_tile(S0, P0);
        wg_wait<0>(); pin(S1);
        const int mlast = P.nstage - 1;
        int m = 0, mnext = 15;
        mbar_wait(bar + B_KVF + 8, 0);
#pragma unroll 1
        while (true) {
            bool ok, plain;
#pragma unroll 1
            do {
                mbar_arrive_cl(rbar + B_KVE + 8 * (m & 3), 1, relp);
                m++;
                const uint32_t d = d0 + (m & 3) * 1024, dv = dv0 + (m & 3) * (1024 * VSTEP);
                issue_step(S0, q, O, P0, d, dv, (m & 15) != 1);
                exp_tile(S1, P1);
                wg_wait<0>(); pin(S0); pin(O);
                issue_step(S1, q, O, P1, d + 256, dv + 256 * VSTEP);
                ok = mbar_test(bar + B_KVF + 8 * ((m + 1) & 3), ((m + 1) >> 2) & 1);
                plain = ok & (m != mnext);
                exp_tile(S0, P0);
                wg_wait<0>(); pin(S1); pin(O);
            } while (plain);
            const int p = m >> 4;
            if (m == mnext) mnext = (m & 15) ? m + 1 : m < 48 ? m + 15 : mlast;
            if ((m & 15) == 0) {
                uint4 v0, v1;
                if (finish_pass(O, g_ob + (ooff + (p - 1) * 256), v0, v1)) {
                    if (lane == 0) mbar_arrive(bar + B_PUBA + 8 * (p - 1));
                } else {
                    fail |= 1u << (p - 1);
                    g_q[(2 * p - 2) * QS + blockIdx.x * 256 + tid] = make_uint4(qn[0], qn[1], qn[2], qn[3]);
                    g_q[(2 * p - 1) * QS + blockIdx.x * 256 + tid] = make_uint4(qn[4], qn[5], qn[6], qn[7]);
                }
                if (p < 3) {
                    const uint4 a = __ldcg(g_q + (2 * p + 2) * QS + blockIdx.x * 256 + tid), b = __ldcg(g_q + (2 * p + 3) * QS + blockIdx.x * 256 + tid);
                    qn[0] = a.x; qn[1] = a.y; qn[2] = a.z; qn[3] = a.w; qn[4] = b.x; qn[5] = b.y; qn[6] = b.z; qn[7] = b.w;
                }
                pin(qn);
            } else if ((m & 15) == 15 && p < 3) {
#pragma unroll
                for (int k = 0; k < 8; k++) { const uint32_t x = q[k]; q[k] = qn[k]; qn[k] = x; }
                pin(q); pin(qn);
            }
            if (!ok) mbar_wait(bar + B_KVF + 8 * ((m + 1) & 3), ((m + 1) >> 2) & 1);
            if (m == mlast) break;
        }
        {
            const int ks = (m + 1) & 3;
            const uint32_t dv = dv0 + ks * (1024 * VSTEP);
            mbar_arrive_cl(rbar + B_KVE + 8 * (m & 3), 1, relp);
            float4 pt[5] = {};
            if (mlast < 63) {
                mbar_wait(bar + B_PART, 0);
#pragma unroll
                for (int c = 0; c < 5; c++) pt[c] = __ldcg(g_part + (blockIdx.x * 2 + w) * 640 + c * 128 + (tid & 127));
            }
            wg_fence(); issue_pv(O, P0, dv); wg_commit();
            exp_tile(S1, P1);
            wg_wait<0>(); pin(O);
            wg_fence(); issue_pv(O, P1, dv + 256 * VSTEP); wg_commit();
            wg_wait<0>(); pin(O);
            mbar_arrive_cl(rbar + B_KVE + 8 * ks, 1, relp);
#pragma unroll
            for (int c = 0; c < 4; c++) { O[4 * c] += pt[c].x; O[4 * c + 1] += pt[c].y; O[4 * c + 2] += pt[c].z; O[4 * c + 3] += pt[c].w; }
            O[16] += pt[4].x; O[18] += pt[4].y;
        }
        uint4 v0, v1;
        if (finish_pass(O, g_ob + (ooff + 768), v0, v1)) release_last(sb, v0, v1, P.nstage); else fail |= 8u;
        if (fail) {
            mbar_wait(bar + B_ALLKV, 0);
            const unsigned k0t = (lds32(bar + B_EPOCH) + 1) * 64;
            while ((int)(ld_acq(g_flag + F_K0) - k0t) < 0) {}
#pragma unroll 1
            for (int p = 0; p < 4; p++) {
                if ((fail >> p) & 1) {
                    const uint4 a = __ldcg(g_q + 2 * p * QS + blockIdx.x * 256 + tid), b = __ldcg(g_q + (2 * p + 1) * QS + blockIdx.x * 256 + tid);
                    const uint32_t qq[8] = {a.x, a.y, a.z, a.w, b.x, b.y, b.z, b.w};
                    uint4 u0, u1;
                    slow_pass(qq, g_ob + (ooff + p * 256), u0, u1);
                    if (p == 3) release_last(sb, u0, u1, P.nstage); else if (lane == 0) mbar_arrive(bar + B_PUBA + 8 * p);
                }
            }
        }
    } else if (warp < 12) {
        const int wq = warp & 3, g = lane >> 2, t = lane & 3;
        const bool relp = lane == 0 && wq < 2;
        const uint32_t rempty = mapa(bar + B_EMPTY, wq & 1);
        const uint32_t stg = sb + OFF_STG;
        {
            const int tq = tid & 127;
            const uint4* src = (bj < 4 ? P.wk : P.wv) + rank * 2048 + tq;
            const uint32_t dst = stg + (tq >> 2) * 64 + (((tq ^ (tq >> 3)) & 3) << 4);
#pragma unroll
            for (int c = 0; c < 16; c++)
                asm volatile("cp.async.cg.shared.global [%0], [%1], 16;" :: "r"(dst + c * 2048), "l"(src + c * 128) : "memory");
            if (tq < 66) reinterpret_cast<float4*>(g_acc)[blockIdx.x * 66 + tq] = make_float4(0.f, 0.f, 0.f, 0.f);
            if (tq == 0) mbar_expect(bar + B_RED, 4096);
            float acc[16];
            zero(acc);
            asm volatile("cp.async.wait_all;" ::: "memory");
            fence_async_smem();
            wg_bar(1);
            const uint32_t dx = mkdesc(OFF_KV, 16), dw = mkdesc(OFF_STG, 512);
#pragma unroll
            for (int c = 0; c < 8; c++) {
                mbar_wait(bar + B_XS - 8 * c, 0);
                wg_fence();
#pragma unroll
                for (int ks = 0; ks < 4; ks++) mma_ss32(acc, dx + c * 512 + ks * 2, dw + c * 256 + ks * 64);
            }
            wg_commit();
            wg_wait<0>();
            pin(acc);
            if (lane == 0) mbar_arrive(bar + B_KVMMA);
#pragma unroll
            for (int c = 0; c < NKV; c++) mbar_arrive_cl(rempty + B_KVE - B_EMPTY + 8 * c, 1, relp);
            mbar_arrive_cl(rempty + B_KVBOTH - B_EMPTY, 1, relp);
            mbar_wait(bar + B_KVBOTH, 0);
            const uint32_t peer = mapa(stg + tq * 16, rank ^ 1), pbar = mapa(bar + B_RED, rank ^ 1);
            float v[8];
#pragma unroll
            for (int c = 0; c < 4; c++) { v[2 * c] = rank ? acc[4 * c] : acc[4 * c + 2]; v[2 * c + 1] = rank ? acc[4 * c + 1] : acc[4 * c + 3]; }
            st_async4(peer, make_uint4(__float_as_uint(v[0]), __float_as_uint(v[1]), __float_as_uint(v[2]), __float_as_uint(v[3])), pbar);
            st_async4(peer + 2048, make_uint4(__float_as_uint(v[4]), __float_as_uint(v[5]), __float_as_uint(v[6]), __float_as_uint(v[7])), pbar);
            mbar_wait(bar + B_RED, 0);
            uint32_t r[8];
            lds128(stg + tq * 16, r[0], r[1], r[2], r[3]); lds128(stg + 2048 + tq * 16, r[4], r[5], r[6], r[7]);
#pragma unroll
            for (int c = 0; c < 4; c++) {
                v[2 * c] = (rank ? acc[4 * c + 2] : acc[4 * c]) + __uint_as_float(r[2 * c]);
                v[2 * c + 1] = (rank ? acc[4 * c + 3] : acc[4 * c + 1]) + __uint_as_float(r[2 * c + 1]);
            }
            const int ro = bi * 128 + th * 64 + wq * 16 + rank * 8 + g, sw = g >> 1;
            uint32_t* row = reinterpret_cast<uint32_t*>(g_kv) + ((bj >> 2) * 2048 + ro) * 16;
            const uint4 u = make_uint4(pack(v[0], v[1]), pack(v[2], v[3]), pack(v[4], v[5]), pack(v[6], v[7]));
            if (bj < 4) {
#pragma unroll
                for (int c = 0; c < 4; c++) row[(c ^ sw) * 4 + t] = pack(v[2 * c] * QSCALE, v[2 * c + 1] * QSCALE);
            } else {
                *reinterpret_cast<uint4*>(row + (t ^ sw) * 4) = u;
            }
            wg_bar(1);
            if (tq == 0) { publish(g_flag + F_KV + ((bj >> 2) * 16 + bi) * 32); }
            __syncwarp();
            if (lane == 0) mbar_arrive(bar + B_PUBG);
            mbar_wait(bar + B_QDONE, 0);
            if (bj < 4) {
                g_q[K0 + ro * 4 + t] = u;
                wg_bar(1);
                if (tq == 0) publish(g_flag + F_K0);
                __syncwarp();
            }
        }
        asm volatile("setmaxnreg.inc.sync.aligned.u32 184;");
        float a0[64], a1[64];
#pragma unroll 1
        for (int seg = 1;; seg++) {
            if (seg == 2) {
                mbar_wait(bar + B_ALLKV, 0);
                gemm_paced<true>(a0, a1, sb, 16, rempty, relp, g_acc + (bj * 4 + (lane >> 4)) * 1056 + 1024 + (lane & 15) * 2, false);
            } else gemm_paced<false>(a0, a1, sb, seg == 5 ? 12 : 16, rempty, relp, nullptr, seg == 4);
            if (seg == 5) break;
            if (seg == 2) {
                uint32_t p0[32], p1[32];
                fence_async_smem();
                frag_pack(a0, p0); frag_pack(a1, p1);
                wg_bar(1);
                float kv0[32], kv1[32];
                wg_fence();
                issue_kv(kv0, p0, OFF_STG); issue_kv(kv1, p1, OFF_STG + 16384);
                wg_commit();
                wg_wait<0>();
                pin(kv0); pin(kv1);
                float* hp = g_acc + (bj * 4 + (wq >> 1)) * 1056 + ((wq & 1) * 16 + g) * 32 + 8 * t;
                red_kv(kv0, wq & 2, hp); red_kv(kv1, wq & 2, hp + 2112);
                __syncwarp();
                if (lane == 0) mbar_arrive(bar + B_PUBG);
            } else if (seg == 3) {
                lin_out(a0, a1, sb, g_oa + (size_t)(bi * 128 + wq * 16 + g) * 1024 + bj * 128 + t * 8, sb + (wq * 16 + g) * 128 + ((t ^ g) << 4));
                fence_async_smem();
                wg_bar(1);
                if (lane == 0) {
                    mbar_arrive(bar + B_PUBG);
                    if (wq < 2) {
                        mbar_wait(bar + B_EMPTY + 16 + 8 * wq, 1);
                        bulk_s2s(sb + (2 + wq) * 16384, sb + wq * 16384, 16384, bar + B_FULL + 16 + 8 * wq, rank ^ 1);
                    }
                }
                __syncwarp();
            } else {
                stage_tile(a0, stg, wq * 16);
                stage_tile(a1, stg, 64 + wq * 16);
                fence_async_smem();
                wg_bar(1);
                if (seg > 1 && (tid & 127) == 0) {
#pragma unroll
                    for (int c = 0; c < 4; c++) tma_st(&P.out, stg + c * 8192, bj * 128 + (c >> 1) * 64, bi * 128 + (c & 1) * 64);
                    asm volatile("cp.async.bulk.commit_group;" ::: "memory");
                }
            }
        }
        if ((tid & 127) == 0) asm volatile("cp.async.bulk.wait_group.read 0;" ::: "memory");
        wg_bar(1);
        {
            const uint32_t dw = mkdesc(OFF_B, BLK), dq = mkdesc(OFF_OWN, 16), dr = mkdesc(OFF_KV, 16) - 1024;
            mbar_wait(bar + B_FULL, 1); mbar_wait(bar + B_LAST + 32, 0);
            fence_async_smem();
            wg_fence();
#pragma unroll
            for (int ks = 0; ks < 4; ks++) mma_ss128(a1, dq + 512 + ks * 2, dw + ks * 128);
#pragma unroll
            for (int s = 1; s < 4; s++) {
                mbar_wait(bar + B_FULL + 8 * s, 1); mbar_wait(bar + B_LAST + 32 + 8 * s, 0);
                wg_fence();
#pragma unroll
                for (int ks = 0; ks < 4; ks++) mma_ss128(a1, dr + s * 1024 + 512 + ks * 2, dw + s * 1024 + ks * 128);
            }
            wg_commit();
            mbar_wait(bar + B_LAST, 0);
            fence_async_smem();
            wg_fence();
#pragma unroll
            for (int ks = 0; ks < 4; ks++) mma_ss128(a0, dq + ks * 2, dw + ks * 128);
            wg_commit();
            wg_wait<1>(); pin(a1);
#define A0(s, ks) mma_ss128(a0, dr + (s) * 1024 + (ks) * 2, dw + (s) * 1024 + (ks) * 128)
            mbar_wait(bar + B_LAST + 8, 0);
            wg_fence();
            A0(1, 0); A0(1, 1); stage_tile<0, 4>(a1, stg, 64 + wq * 16);
            A0(1, 2); stage_tile<4, 8>(a1, stg, 64 + wq * 16);
            A0(1, 3); stage_tile<8, 12>(a1, stg, 64 + wq * 16);
            mbar_wait(bar + B_LAST + 16, 0);
            wg_fence();
            A0(2, 0); stage_tile<12, 16>(a1, stg, 64 + wq * 16);
            A0(2, 1); A0(2, 2); A0(2, 3);
            fence_async_smem();
            wg_bar(1);
            if (wq == 0 && elect()) {
                tma_st(&P.out, stg + 8192, 1024 + bj * 128, bi * 128 + 64); tma_st(&P.out, stg + 24576, 1024 + bj * 128 + 64, bi * 128 + 64);
                asm volatile("cp.async.bulk.commit_group;" ::: "memory");
            }
            __syncwarp();
            mbar_wait(bar + B_LAST + 24, 0);
            wg_fence();
            A0(3, 0); A0(3, 1); A0(3, 2); A0(3, 3);
#undef A0
            wg_commit();
            mbar_arrive_cl(rempty + B_FIN - B_EMPTY, 1, relp);
            wg_wait<0>(); pin(a0);
            stage_tile(a0, stg, wq * 16);
            __syncwarp();
            uint4* o = P.outp + (size_t)(bi * 128 + wq * 16 + (lane >> 4)) * 256 + 128 + bj * 16 + (lane & 15);
            const uint32_t a = stg + ((lane >> 3) & 1) * 16384 + (wq * 16 + (lane >> 4)) * 128 + (((lane & 7) ^ (lane >> 4)) << 4);
#pragma unroll
            for (int r = 0; r < 8; r++) {
                uint4 v;
                lds128((a ^ (((2 * r) & 7) << 4)) + r * 256, v.x, v.y, v.z, v.w);
                o[r * 512] = v;
            }
            if (wq == 0) asm volatile("cp.async.bulk.wait_group.read 0;" ::: "memory");
        }
    } else {
        asm volatile("setmaxnreg.dec.sync.aligned.u32 24;");
        if (warp == 12) {
            const int arow = bi * 128 + rank * 64, pj = bj >> 1;
#pragma unroll 1
            for (int it = 0; it < 20; it++) {
                const int s = it & (NS - 1), kb = (it & 1) * 8 + (it >> 1);
                const uint32_t fb = bar + B_FULL + 8 * s;
                const bool own = (it & 1) == rank;
                if (it >= NS) {
                    mbar_wait_wd(bar + B_EMPTY + 8 * s, ((it >> 2) & 1) ^ 1);
                    if (s == NS - 1 && elect()) mbar_arrive_cl(bar + B_KVE + 8 * ((it >> 2) - 1), 2, true);
                    if (it >= 16) continue;
                    if (elect()) {
                        mbar_expect(fb, own ? STAGE - 8192 : STAGE);
                        if (!own) tma_ld_mc(sb + s * 16384 + (th ^ 1) * 8192, &P.xB, kb * 64, bi * 128 + (th ^ 1) * 64, fb);
                        tma_ld_w(sb + OFF_B + s * 16384, &P.wq, 0, 2 * kb, bj * 2, fb);
                        if (it < NS + 2) {
#pragma unroll
                            for (int c2 = 0; c2 < 2; c2++) {
                                const int c = 2 * it - 4 + c2;
                                mbar_expect(bar + B_XS - 8 * c, 8192);
                                tma_ld(sb + OFF_KV + c * 8192, &P.xB, rank * 512 + c * 64, bi * 128 + th * 64, bar + B_XS - 8 * c);
                            }
                        }
                    }
                }
                if (own) {
                    mbar_wait_wd(bar + B_XS - 8 * (it >> 1), 0);
                    if (elect()) bulk_s2s(sb + s * 16384 + th * 8192, sb + OFF_KV + (it >> 1) * 8192, 8192, fb, rank ^ 1);
                }
            }
            mbar_wait_wd(bar + B_GO, 0);
#pragma unroll 1
            for (int it = 16; it < 64; it++) {
                const int s = it & (NS - 1), kb = it & 15, tile = it >> 4;
                mbar_wait_wd(bar + B_EMPTY + 8 * s, ((it >> 2) & 1) ^ 1);
                if (elect()) {
                    const uint32_t fb = bar + B_FULL + 8 * s;
                    mbar_expect(fb, STAGE);
                    tma_ld_mc(sb + s * 16384 + rank * 8192, &P.xA, kb * 64, arow, fb);
                    tma_ld_w(sb + OFF_B + s * 16384, &P.wqkv, 0, 2 * kb, bj * 2 + (tile == 3 ? 0 : tile * 16), fb);
                }
            }
            mbar_wait_wd(bar + B_ALLKV, 0);
            const unsigned epoch = lds32(bar + B_EPOCH);
#pragma unroll 1
            for (int it = 0; it < 32; it++) {
                const int s = it & (NS - 1), g4 = (it >> 2) & 3;
                const bool tb = it >= 16, noa = it < NS || it >= 28;
                if (s == 0 && !noa) {
                    poll(g_flag + (tb ? F_OB + g4 : F_OA + ((pj + g4) & 3)) + 32 * bi, (epoch + 1) * (tb ? 8 : 2));
                    fence_async_gmem();
                }
                const int kb = tb ? g4 * 4 + ((pj + s) & 3) : ((pj + g4) & 3) * 4 + (it < NS ? s ^ (rank * 2) : s);
                mbar_wait_wd(bar + B_EMPTY + 8 * s, (g4 & 1) ^ 1);
                if (elect()) {
                    const uint32_t fb = bar + B_FULL + 8 * s;
                    mbar_expect(fb, it < 2 || it >= 28 ? 16384 : STAGE);
                    if (!noa) tma_ld_mc(sb + s * 16384 + rank * 8192, tb ? &P.ob : &P.oa, kb * 64, arow, fb);
                    tma_ld_w(sb + OFF_B + s * 16384, tb ? &P.woB : &P.woA, tb ? g4 * 32 : 0, tb ? 2 * (kb & 3) : 2 * kb, bj * 2, fb);
                }
            }
            mbar_wait_wd(bar + B_FIN, 0);
            if (lane == 0) atomicAdd(g_flag + F_DONE, 1u);
        } else if (warp == 13) {
            if (lane < 7) asm volatile("prefetch.tensormap [%0];" :: "l"(&P.xA + lane) : "memory");
            __syncwarp();
            const unsigned target = ((*reinterpret_cast<volatile unsigned*>(g_flag + F_DONE) >> 7) + 1) * 4;
            mbar_wait_wd(bar + B_PUBG, 0);
            if (lane == 0) mbar_arrive(bar + B_KVPUB);
            __syncwarp();
            if (lane < 8) mbar_expect(bar + B_LAST + 8 * lane, 8192);
            __syncwarp();
            int tl = (bi + (rank ? 15 : 0)) & 15, s = 0, ph = 0;
            uint32_t have = 0;
#pragma unroll 1
            for (int it = 0; it <= P.nstage; it++) {
                const bool mine = it != (rank ? 0 : P.nstage);
                if (mine && !((have >> tl) & 1)) {
                    uint32_t n = 0, t0 = 0;
                    do {
                        const bool look = lane < 16 && ((lane - tl) & 15) < (it > rank ? 16 : 3);
                        have = __ballot_sync(0xffffffffu, look && (int)(ld_acq(g_flag + F_KV + (rank * 16 + lane) * 32) - target) >= 0);
                        watchdog(n, t0);
                    } while (!((have >> tl) & 1));
                    __syncwarp();
                    fence_async_gmem();
                }
                mbar_wait_wd(bar + B_KVE + 8 * s, ph);
                if (elect()) {
                    mbar_expect(bar + B_KVF + 8 * s, it == 0 || it == P.nstage ? KVB / 2 : KVB);
                    if (it == 5) mbar_arrive(bar + B_GO);
                    if (mine) bulk_ld_mc(sb + OFF_KV + s * KVB + rank * 8192, g_kv + (rank * 2048 + tl * 128) * 32, 8192, bar + B_KVF + 8 * s);
                }
                tl = (tl + 1) & 15;
                if (++s == NKV) { s = 0; ph ^= 1; }
            }
#pragma unroll 1
            for (int it = 0; it < NKV; it++) {
                mbar_wait_wd(bar + B_KVE + 8 * s, ph);
                if (++s == NKV) { s = 0; ph ^= 1; }
            }
            const unsigned* fl = g_flag + F_OB + 32 * bi + 4 + rank * 4 + (((bj >> 1) + 1 + lane) & 3);
            uint32_t pend = 7, n = 0, t0 = 0;
            do {
                const uint32_t go = __ballot_sync(0xffffffffu, (int)(ld_acq(fl) - target * 2) >= 0) & pend;
                if (go) {
                    __syncwarp();
                    fence_async_gmem();
                    if (elect()) {
#pragma unroll
                        for (int c = 0; c < 3; c++)
                            if ((go >> c) & 1) {
                                tma_ld_mc(sb + OFF_KV + c * 16384 + rank * 8192, &P.ob, (12 + (((bj >> 1) + 1 + c) & 3)) * 64, bi * 128 + rank * 64, bar + B_LAST + rank * 32 + 8 + 8 * c);
                            }
                    }
                    pend &= ~go;
                }
                watchdog(n, t0);
            } while (pend);
        } else if (warp == 14) {
            const unsigned epoch = *reinterpret_cast<volatile unsigned*>(g_flag + F_DONE) >> 7;
            mbar_wait_wd(bar + B_KVPUB, 0);
            __nanosleep(4000);
            {
                uint32_t n = 0, t0 = 0;
                while (!__all_sync(0xffffffffu, (int)(ld_acq(g_flag + F_KV + lane * 32) - (epoch + 1) * 4) >= 0)) watchdog(n, t0);
            }
            __syncwarp();
            if (lane == 0) {
                asm volatile("st.shared.u32 [%0], %1;" :: "r"(bar + B_EPOCH), "r"(epoch) : "memory");
                mbar_arrive(bar + B_ALLKV);
            }
            __syncwarp();
            mbar_wait_wd(bar + B_PUBG, 1);
            if (lane == 0) publish(g_flag + F_SUM + 32 * bj);
            __syncwarp();
            poll(g_flag + F_SUM + 32 * bj, (epoch + 1) * 16);
            if (lane == 0) { mbar_arrive(bar + B_SUM); }
            __syncwarp();
            prep_operand(sb, g_acc + bj * 4 * 1056, 0);
            mbar_wait_wd(bar + B_PUBG, 0);
            if (lane == 0) publish(g_flag + F_OA + 32 * bi + (bj >> 1));
            if (P.nstage < 64 && lane == 0) {
                uint32_t n = 0, t0 = 0;
                while ((int)(ld_acq(g_flag + F_PART + (bi >> 2) * 32) - (epoch + 1)) < 0) { __nanosleep(500); watchdog(n, t0); }
                mbar_arrive(bar + B_PART);
            }
        } else {
            mbar_wait_wd(bar + B_Q3, 0);
            if (lane == 0) publish(g_flag + F_Q3 + blockIdx.x);
            __syncwarp();
            mbar_wait_wd(bar + B_SUM, 0);
            prep_operand(sb, g_acc + bj * 4 * 1056, 2);
#pragma unroll 1
            for (int p = 0; p < 3; p++) {
                mbar_wait_wd(bar + B_PUBA + 8 * p, 0);
                if (lane == 0) publish(g_flag + F_OB + 32 * bi + p);
                __syncwarp();
            }
        }
    }
}

typedef CUresult (*EncodeFn)(CUtensorMap*, CUtensorMapDataType, cuuint32_t, void*, const cuuint64_t*, const cuuint64_t*,
                             const cuuint32_t*, const cuuint32_t*, CUtensorMapInterleave, CUtensorMapSwizzle,
                             CUtensorMapL2promotion, CUtensorMapFloatOOBfill);

void make_map(EncodeFn enc, CUtensorMap* m, const void* p, int rows, int cols, int box_rows, int box_cols, CUtensorMapSwizzle sw, CUtensorMapL2promotion pr = CU_TENSOR_MAP_L2_PROMOTION_L2_256B) {
    cuuint64_t gd[2] = {(cuuint64_t)cols, (cuuint64_t)rows};
    cuuint64_t gs[1] = {(cuuint64_t)cols * 2};
    cuuint32_t bd[2] = {(cuuint32_t)box_cols, (cuuint32_t)box_rows};
    cuuint32_t es[2] = {1, 1};
    enc(m, CU_TENSOR_MAP_DATA_TYPE_BFLOAT16, 2, const_cast<void*>(p), gd, gs, bd, es, CU_TENSOR_MAP_INTERLEAVE_NONE, sw,
        pr, CU_TENSOR_MAP_FLOAT_OOB_FILL_NONE);
}

void make_wmap(EncodeFn enc, CUtensorMap* m, const void* p, int cols, int grp_rows) {
    cuuint64_t gd[4] = {64, (cuuint64_t)grp_rows, (cuuint64_t)(1024 / grp_rows), (cuuint64_t)(cols / 64)};
    cuuint64_t gs[3] = {(cuuint64_t)cols * 2, (cuuint64_t)cols * 2 * grp_rows, 128};
    cuuint32_t bd[4] = {64, 32, 2, 2};
    cuuint32_t es[4] = {1, 1, 1, 1};
    enc(m, CU_TENSOR_MAP_DATA_TYPE_BFLOAT16, 4, const_cast<void*>(p), gd, gs, bd, es, CU_TENSOR_MAP_INTERLEAVE_NONE,
        CU_TENSOR_MAP_SWIZZLE_128B, CU_TENSOR_MAP_L2_PROMOTION_L2_256B, CU_TENSOR_MAP_FLOAT_OOB_FILL_NONE);
}

}

extern "C" void kernel_launch(void* const* d_in, const int* in_sizes, int n_in, void* d_out, int out_size) {
    EncodeFn enc = nullptr;
    cudaDriverEntryPointQueryResult qr;
    cudaGetDriverEntryPoint("cuTensorMapEncodeTiled", (void**)&enc, cudaEnableDefault, &qr);
    Scratch* sc;
    cudaGetSymbolAddress((void**)&sc, g_s);
    Params P;
    const CUtensorMapSwizzle S128 = CU_TENSOR_MAP_SWIZZLE_128B;
    make_map(enc, &P.xA, d_in[0], 2048, 1024, 64, 64, S128);
    make_wmap(enc, &P.wqkv, d_in[1], 3072, 32);
    make_wmap(enc, &P.woA, d_in[2], 1024, 32);
    make_map(enc, &P.xB, d_in[3], 2048, 1024, 64, 64, S128);
    make_wmap(enc, &P.wq, d_in[4], 1024, 32);
    P.outp = (uint4*)d_out;
    P.wk = (const uint4*)d_in[5];
    P.wv = (const uint4*)d_in[6];
    make_wmap(enc, &P.woB, d_in[7], 1024, 128);
    make_map(enc, &P.oa, sc->oa, 2048, 1024, 64, 64, S128, CU_TENSOR_MAP_L2_PROMOTION_L2_128B);
    make_map(enc, &P.ob, sc->ob, 2048, 1024, 64, 64, S128, CU_TENSOR_MAP_L2_PROMOTION_L2_128B);
    make_map(enc, &P.out, d_out, 2048, 2048, 64, 64, S128);
    cudaFuncSetAttribute(fused_kernel, cudaFuncAttributeMaxDynamicSharedMemorySize, SMEM_BYTES);
    cudaLaunchConfig_t cfg = {};
    cfg.gridDim = dim3(132); cfg.blockDim = dim3(512); cfg.dynamicSmemBytes = SMEM_BYTES;
    cudaLaunchAttribute at;
    at.id = cudaLaunchAttributeClusterDimension; at.val.clusterDim.x = 2; at.val.clusterDim.y = 1; at.val.clusterDim.z = 1;
    cfg.attrs = &at; cfg.numAttrs = 1;
    int ncl = 0;
    if (cudaOccupancyMaxActiveClusters(&ncl, fused_kernel, &cfg) != cudaSuccess) { ncl = 0; cudaGetLastError(); }
    P.nstage = ncl >= 66 ? 62 : 64;
    fused_kernel<<<ncl >= 66 ? 132 : 128, 512, SMEM_BYTES>>>(P);
}
```
